```python
import torch

def _softmax(x, axis=-1):
    return torch.softmax(x, dim=axis)

def _gelu(x):
    return torch.nn.functional.gelu(x, approximate='tanh')

def _silu(x):
    return torch.nn.functional.silu(x)

def _sigmoid(x):
    return torch.sigmoid(x)

def _layernorm(x, axis=-1, eps=1e-05):
    m = x.mean(dim=axis, keepdim=True)
    v = x.var(dim=axis, keepdim=True, unbiased=False)
    return (x - m) / torch.sqrt(v + eps)

def _scatter_add(tgt, idx, src, axis=0):
    return tgt.clone().index_add_(axis, idx, src)

def _segment_sum(src, seg, n):
    out = torch.zeros((n,) + src.shape[1:], dtype=src.dtype)
    return out.index_add_(0, seg, src)

def _pad(x, pw):
    flat = tuple((v for pair in reversed(pw) for v in pair))
    return torch.nn.functional.pad(x, flat)
kernel_name = 'gated_mix__memory_aug_recurrent_mem_tr__sliding_block__prompt'

def setup_inputs():

    _w = lambda a: (lambda t: t.to(torch.bfloat16) if t.is_floating_point() else t)(torch.as_tensor(a))

    def _A_setup():
        B, S, Dm = (1, 2048, 576)
        H, Dh = (32, 128)
        M, seg = (8, 32)
        seg = min(seg, S)
        S = S // seg * seg
        return {'x': _w((lambda *s: torch.randn(*s, dtype=torch.bfloat16) * 0.05)(B, S, Dm)), 'mem0': _w((lambda *s: torch.randn(*s, dtype=torch.bfloat16) * 1.6)(B, M, Dm)), 'Wq': _w((lambda *s: torch.randn(*s, dtype=torch.bfloat16) * 0.8)(Dm, H, Dh) * Dm ** (-0.5)), 'Wk': _w((lambda *s: torch.randn(*s, dtype=torch.bfloat16) * 0.8)(Dm, H, Dh) * Dm ** (-0.5)), 'Wv': _w((lambda *s: torch.randn(*s, dtype=torch.bfloat16) * 1.6)(Dm, H, Dh) * Dm ** (-0.5)), 'Wo': _w((lambda *s: torch.randn(*s, dtype=torch.bfloat16) * 1.6)(H, Dh, Dm) * (H * Dh) ** (-0.5)), 'seg_len': seg}
    _A_in = _A_setup()

    def _B_setup():
        B, S, D = (1, 2048, 576)
        return {'x': _w((lambda *s: torch.randn(*s, dtype=torch.bfloat16) * 0.05)(B, S, D)), 'wqkv': _w((lambda *s: torch.randn(*s, dtype=torch.bfloat16) * 1.6)(D, 3 * D)), 'wo': _w((lambda *s: torch.randn(*s, dtype=torch.bfloat16) * 0.05)(D, D))}
    _B_in = _B_setup()
    return {'A_x': _A_in['x'], 'A_mem0': _A_in['mem0'], 'A_Wq': _A_in['Wq'], 'A_Wk': _A_in['Wk'], 'A_Wv': _A_in['Wv'], 'A_Wo': _A_in['Wo'], 'A_seg_len': _A_in['seg_len'], 'B_x': _B_in['x'], 'B_wqkv': _B_in['wqkv'], 'B_wo': _B_in['wo'], 'gate_w': _w((lambda *s: torch.randn(*s, dtype=torch.bfloat16) * 0.05)(576) * 16.0)}

def reference(A_x, A_mem0, A_Wq, A_Wk, A_Wv, A_Wo, A_seg_len, B_x, B_wqkv, B_wo, gate_w):

    def _A_ref(x, mem0, Wq, Wk, Wv, Wo, seg_len):
        B, S, Dm = x.shape
        H, Dh = (Wq.shape[1], Wq.shape[2])
        M = mem0.shape[1]
        scale = Dh ** (-0.5)
        n_seg = S // seg_len
        L = M + seg_len
        idx = torch.arange(L)
        mask = (idx[:, None] < M) | (idx[:, None] >= idx[None, :])
        mem = mem0
        outs = []
        for s in range(n_seg):
            xs = x[:, s * seg_len:(s + 1) * seg_len, :].clone()
            h = torch.concatenate([mem, xs], axis=1)
            q = torch.einsum('btd,dhe->bhte', h, Wq)
            k = torch.einsum('btd,dhe->bhte', h, Wk)
            v = torch.einsum('btd,dhe->bhte', h, Wv)
            scores = torch.einsum('bhqe,bhke->bhqk', q, k) * scale
            scores = torch.where(mask[None, None], scores, -1000000000.0)
            p = _softmax(scores, axis=-1)
            o = torch.einsum('bhqk,bhke->bhqe', p, v)
            o = torch.einsum('bhte,hed->btd', o, Wo)
            mem = o[:, :M, :].clone()
            outs.append(o[:, M:, :])
        return torch.concatenate(outs, axis=1)

    def _B_ref(x, wqkv, wo):
        B, S, D = x.shape
        H = 32
        Dh = D // H
        W = 256
        qkv = (lambda x, *d: x.permute(*d))((x @ wqkv).reshape(B, S, 3, H, Dh), 2, 0, 3, 1, 4)
        q, k, v = (qkv[0], qkv[1], qkv[2])
        scores = torch.einsum('bhqd,bhkd->bhqk', q, k) * Dh ** (-0.5)
        idx = torch.arange(S)
        mask = (idx[:, None] - idx[None, :] >= 0) & (idx[:, None] - idx[None, :] < W)
        scores = torch.where(mask[None, None], scores, -1000000000.0)
        p = _softmax(scores, axis=-1)
        o = torch.einsum('bhqk,bhkd->bhqd', p, v)
        return (lambda x, *d: x.permute(*d))(o, 0, 2, 1, 3).reshape(B, S, D) @ wo
    x = A_x
    g = _sigmoid((x * gate_w).sum(-1, keepdims=True))
    a = _A_ref(x, A_mem0, A_Wq, A_Wk, A_Wv, A_Wo, A_seg_len)
    b = _B_ref(x, B_wqkv, B_wo)
    return g * a + (1 - g) * b
```

```cpp
#include <cuda_runtime.h>
#include <cuda_bf16.h>
#include <cuda.h>
#include <stdint.h>

typedef __nv_bfloat16 bf16;
#define DOX 1
#define DOFENCE 1
#define USE_PDL 0
constexpr unsigned SEGFLAG_N=96*8;
constexpr int SEQ=2048, DM=576, NH=32, DH=128, NSEG=64;

__device__ uint4 g_acc[NSEG*768];
__device__ uint4 g_qx[NSEG*NH*512];
__device__ uint4 g_kx[NSEG*NH*512];
__device__ uint4 g_vx[NSEG*NH*512];
__device__ uint2 g_km[NSEG*NH*256];
__device__ uint2 g_vm[NSEG*NH*256];
__device__ unsigned g_bar_cnt, g_bar_gen;
__device__ unsigned g_tmax[NSEG*32];
__device__ unsigned g_tbase;
__device__ unsigned g_norm[2*96];
__device__ unsigned g_segflag[NSEG*32];
__device__ int g_pK=400, g_pE=200, g_pXq=1;
__device__ __forceinline__ unsigned gtime(){ unsigned v; asm volatile("mov.u32 %0, %%globaltimer_lo;":"=r"(v)::"memory"); return v; }
#define TS(idx)
#define TSD(idx,dep)
__device__ int g_pD = 800, g_pS = 50;

__device__ __forceinline__ uint32_t smem_u32(const void* p){ return (uint32_t)__cvta_generic_to_shared(p); }
__device__ __forceinline__ uint32_t mapa(uint32_t a, int r){ uint32_t o; asm("mapa.shared::cluster.u32 %0,%1,%2;":"=r"(o):"r"(a),"r"(r)); return o; }
__device__ __forceinline__ uint32_t movm(uint32_t a){ uint32_t d; asm volatile("movmatrix.sync.aligned.m8n8.trans.b16 %0,%1;":"=r"(d):"r"(a)); return d; }
__device__ __forceinline__ uint32_t pack2(float lo, float hi){ uint32_t d; asm("cvt.rn.bf16x2.f32 %0,%1,%2;":"=r"(d):"f"(hi),"f"(lo)); return d; }
__device__ __forceinline__ void mma16816(float* d, uint32_t a0,uint32_t a1,uint32_t a2,uint32_t a3, uint32_t b0, uint32_t b1){
  asm volatile("mma.sync.aligned.m16n8k16.row.col.f32.bf16.bf16.f32 {%0,%1,%2,%3},{%4,%5,%6,%7},{%8,%9},{%0,%1,%2,%3};"
   : "+f"(d[0]),"+f"(d[1]),"+f"(d[2]),"+f"(d[3]) : "r"(a0),"r"(a1),"r"(a2),"r"(a3),"r"(b0),"r"(b1));
}
__device__ __forceinline__ void mma1688(float* d, uint32_t a0,uint32_t a1, uint32_t b0){
  asm volatile("mma.sync.aligned.m16n8k8.row.col.f32.bf16.bf16.f32 {%0,%1,%2,%3},{%4,%5},{%6},{%0,%1,%2,%3};"
   : "+f"(d[0]),"+f"(d[1]),"+f"(d[2]),"+f"(d[3]) : "r"(a0),"r"(a1),"r"(b0));
}
__device__ __forceinline__ void ldsm4(uint32_t& r0,uint32_t& r1,uint32_t& r2,uint32_t& r3,uint32_t addr){
  asm volatile("ldmatrix.sync.aligned.m8n8.x4.shared.b16 {%0,%1,%2,%3},[%4];":"=r"(r0),"=r"(r1),"=r"(r2),"=r"(r3):"r"(addr):"memory");
}
__device__ __forceinline__ void ldsm2(uint32_t& r0,uint32_t& r1,uint32_t addr){
  asm volatile("ldmatrix.sync.aligned.m8n8.x2.shared.b16 {%0,%1},[%2];":"=r"(r0),"=r"(r1):"r"(addr):"memory");
}
__device__ __forceinline__ void mbar_init(uint32_t a, int cnt){ asm volatile("mbarrier.init.shared.b64 [%0], %1;"::"r"(a),"r"(cnt):"memory"); }
__device__ __forceinline__ void mbar_expect(uint32_t a, uint32_t tx){ asm volatile("mbarrier.arrive.expect_tx.shared.b64 _, [%0], %1;"::"r"(a),"r"(tx):"memory"); }
__device__ __forceinline__ void mbar_arrive(uint32_t a){ asm volatile("mbarrier.arrive.shared.b64 _, [%0];"::"r"(a):"memory"); }
__device__ __forceinline__ void mbar_wait(uint32_t a, uint32_t par){
  uint32_t done=0; int it=0;
  do { asm volatile("{.reg .pred p; mbarrier.try_wait.parity.shared.b64 p,[%1],%2; selp.u32 %0,1,0,p;}":"=r"(done):"r"(a),"r"(par):"memory"); } while(!done && ++it<(1<<22));
}
__device__ __forceinline__ void mbar_wait_cluster(uint32_t a, uint32_t par){
  uint32_t done=0; int it=0;
  do { asm volatile("{.reg .pred p; mbarrier.try_wait.parity.acquire.cluster.shared.b64 p,[%1],%2; selp.u32 %0,1,0,p;}":"=r"(done):"r"(a),"r"(par):"memory"); } while(!done && ++it<(1<<22));
}
__device__ __forceinline__ void bar_sync(int id, int n){ asm volatile("bar.sync %0,%1;"::"r"(id),"r"(n):"memory"); }
__device__ __forceinline__ void bar_arrive(int id, int n){ asm volatile("bar.arrive %0,%1;"::"r"(id),"r"(n):"memory"); }
__device__ __forceinline__ float4 ld_relaxed_v4(const float4* p){
  float4 v; asm volatile("ld.relaxed.gpu.global.v4.f32 {%0,%1,%2,%3}, [%4];" : "=f"(v.x),"=f"(v.y),"=f"(v.z),"=f"(v.w) : "l"(p) : "memory"); return v;
}
__device__ __forceinline__ uint4 ld_cg_v4(const uint4* p){
  uint4 v; asm volatile("ld.relaxed.gpu.global.v4.u32 {%0,%1,%2,%3}, [%4];" : "=r"(v.x),"=r"(v.y),"=r"(v.z),"=r"(v.w) : "l"(p) : "memory"); return v;
}
__device__ __forceinline__ void red_v4(float4* p, float a, float b, float c, float d){
  asm volatile("red.relaxed.gpu.global.add.v4.f32 [%0], {%1,%2,%3,%4};" :: "l"(p), "f"(a),"f"(b),"f"(c),"f"(d) : "memory");
}
__device__ __forceinline__ void red_h4(uint4* p, uint32_t a, uint32_t b, uint32_t c, uint32_t d){
  asm volatile("red.relaxed.gpu.global.add.noftz.v4.f16x2 [%0], {%1,%2,%3,%4};" :: "l"(p), "r"(a),"r"(b),"r"(c),"r"(d) : "memory");
}
__device__ __forceinline__ uint32_t packh(float lo, float hi){ uint32_t d; asm("cvt.rn.f16x2.f32 %0,%1,%2;":"=r"(d):"f"(hi),"f"(lo)); return d; }
__device__ __forceinline__ uint32_t h2bf(uint32_t h){ float lo,hi; asm("{.reg .f16 a,b; mov.b32 {a,b},%2; cvt.f32.f16 %0,a; cvt.f32.f16 %1,b;}":"=f"(lo),"=f"(hi):"r"(h)); return pack2(lo,hi); }
__device__ __forceinline__ void tma_load_2d(uint32_t dst, const CUtensorMap* tm, int c0, int c1, uint32_t mbar){
  asm volatile("cp.async.bulk.tensor.2d.shared::cluster.global.mbarrier::complete_tx::bytes [%0], [%1, {%3, %4}], [%2];"
    :: "r"(dst), "l"((uint64_t)tm), "r"(mbar), "r"(c0), "r"(c1) : "memory");
}
__device__ __forceinline__ void wgmma_rs_n32(float* d, uint32_t a0,uint32_t a1,uint32_t a2,uint32_t a3, uint64_t desc, int scale_d){
  asm volatile("{.reg .pred p; setp.ne.b32 p, %21, 0;\n"
   "wgmma.mma_async.sync.aligned.m64n32k16.f32.bf16.bf16 {%0,%1,%2,%3,%4,%5,%6,%7,%8,%9,%10,%11,%12,%13,%14,%15}, {%16,%17,%18,%19}, %20, p, 1, 1, 0;}"
   : "+f"(d[0]),"+f"(d[1]),"+f"(d[2]),"+f"(d[3]),"+f"(d[4]),"+f"(d[5]),"+f"(d[6]),"+f"(d[7]),"+f"(d[8]),"+f"(d[9]),"+f"(d[10]),"+f"(d[11]),"+f"(d[12]),"+f"(d[13]),"+f"(d[14]),"+f"(d[15])
   : "r"(a0),"r"(a1),"r"(a2),"r"(a3),"l"(desc),"r"(scale_d));
}
__device__ __forceinline__ unsigned ld_flag(const unsigned* p){ unsigned v; asm volatile("ld.relaxed.gpu.global.u32 %0,[%1];":"=r"(v):"l"(p):"memory"); return v; }
__device__ __forceinline__ void spin_until(unsigned t){ while((int)(clock()-t)<0); }

constexpr int XBUF = 36864;
constexpr int NXB = 3;
constexpr int SM_X = 0;
constexpr int SM_KV = SM_X + NXB*XBUF;
constexpr int SM_WO = SM_KV + 32768;
constexpr int SM_XR = SM_WO + 49152;
constexpr int SM_MEM = SM_XR + 16384;
constexpr int SM_Q = SM_MEM + 8*1168;
constexpr int SM_S = SM_Q + 3*2048;
constexpr int SM_O = SM_S + 8*64*4 + 64;
constexpr int SM_BAR = SM_O + 8*272;
constexpr int SM_CT = SM_BAR + 64;
constexpr int SM_TS = SM_CT + 128;
constexpr int CHAIN_SMEM = SM_TS;
__device__ __forceinline__ float ex2(float x){ float y; asm("ex2.approx.ftz.f32 %0,%1;":"=f"(y):"f"(x)); return y; }
__device__ __forceinline__ float rcpa(float x){ float y; asm("rcp.approx.ftz.f32 %0,%1;":"=f"(y):"f"(x)); return y; }
__device__ __forceinline__ uint4 lds128(uint32_t a){ uint4 v; asm volatile("ld.shared.v4.u32 {%0,%1,%2,%3},[%4];":"=r"(v.x),"=r"(v.y),"=r"(v.z),"=r"(v.w):"r"(a):"memory"); return v; }
__device__ __forceinline__ uint2 lds64(uint32_t a){ uint2 v; asm volatile("ld.shared.v2.u32 {%0,%1},[%2];":"=r"(v.x),"=r"(v.y):"r"(a):"memory"); return v; }
__device__ __forceinline__ void sts32(uint32_t a, uint32_t v){ asm volatile("st.shared.u32 [%0],%1;"::"r"(a),"r"(v):"memory"); }
__device__ __forceinline__ void stsf(uint32_t a, float v){ asm volatile("st.shared.f32 [%0],%1;"::"r"(a),"f"(v):"memory"); }
__device__ __forceinline__ void bulk_g2s(uint32_t dst, const void* src, uint32_t bytes, uint32_t mbar){
  asm volatile("cp.async.bulk.shared::cluster.global.mbarrier::complete_tx::bytes [%0],[%1],%2,[%3];"::"r"(dst),"l"(src),"r"(bytes),"r"(mbar):"memory");
}

__device__ __forceinline__ void sts128f(uint32_t a, float x, float y, float z, float w){ asm volatile("st.shared.v4.f32 [%0],{%1,%2,%3,%4};"::"r"(a),"f"(x),"f"(y),"f"(z),"f"(w):"memory"); }
__device__ __forceinline__ uint32_t lds32(uint32_t a){ uint32_t v; asm volatile("ld.shared.u32 %0,[%1];":"=r"(v):"r"(a):"memory"); return v; }
__device__ __forceinline__ void tma_load_2d_mc(uint32_t dst, const CUtensorMap* tm, int c0, int c1, uint32_t mbar, uint16_t mask){
  asm volatile("cp.async.bulk.tensor.2d.shared::cluster.global.mbarrier::complete_tx::bytes.multicast::cluster [%0], [%1, {%3, %4}], [%2], %5;"
    :: "r"(dst), "l"((uint64_t)tm), "r"(mbar), "r"(c0), "r"(c1), "h"(mask) : "memory");
}
__device__ __forceinline__ float bf_lo(uint32_t v){ return __uint_as_float(v<<16); }
__device__ __forceinline__ float bf_hi(uint32_t v){ return __uint_as_float(v&0xffff0000u); }
#define F(x) __uint_as_float(x)

constexpr int AOW = 4672;
__device__ bf16 g_ao[SEQ*AOW];
__device__ bf16 g_bq[96*SEQ*24];
__device__ float g_gate[SEQ];
constexpr int PSL = 128*288;
__device__ float g_part[(32*5+2*12)*PSL];
__device__ unsigned g_cnt[192*32];
constexpr int C_TASK=0, C_BQ=1, C_BA=17, C_XA=33, C_MODE=97, C_DONE=129, C_GATE=161;
__device__ int g_pWhole = 40;

constexpr int A_STAGE = 16384+5*8192;
constexpr int A_NST = 3;
constexpr int A_BAR = A_NST*A_STAGE;
constexpr int AUX_SMEM = A_BAR + 256;

constexpr int T_GATE=16, T_BQ=96, T_BA=128;
constexpr int T_RB = 16+10;
constexpr int T_LAST = 2*17;
constexpr int T0_BQ=T_GATE, T0_BA=T0_BQ+T_BQ, T0_RB=T0_BA+T_BA;
constexpr int T_TOTAL = T0_RB + 15*T_RB + 16 + T_LAST;

__global__ void __cluster_dims__(3,1,1) __launch_bounds__(384,1)
chain_kernel(const __grid_constant__ CUtensorMap tmx, const bf16* __restrict__ x, const bf16* __restrict__ mem0, const bf16* __restrict__ Wq, const bf16* __restrict__ Wk,
             const bf16* __restrict__ Wv, const bf16* __restrict__ Wo)
{
  extern __shared__ __align__(1024) unsigned char sm[];
  const uint32_t sb = smem_u32(sm);
  const int tid = threadIdx.x, lane = tid&31, warp = tid>>5, g = lane>>2, t = lane&3;
  const int j = blockIdx.x % 3, h = blockIdx.x / 3;
  const uint32_t bar_qkv = sb+SM_BAR, bar_x = sb+SM_BAR+16, bar_kv = sb+SM_BAR+48;
  const uint32_t ct = sb+SM_CT;
  if (tid==0){
    mbar_init(bar_qkv, 9);
    for (int i=0;i<NXB;i++) mbar_init(bar_x+8*i, 1);
    mbar_init(bar_kv,1); mbar_init(bar_kv+8,1);
    asm volatile("fence.mbarrier_init.release.cluster;":::"memory");
    for (int b=0;b<3;b++){ mbar_expect(bar_x+8*b, XBUF); for (int q=0;q<9;q++) tma_load_2d(sb+SM_X+b*XBUF+q*4096,&tmx,q*64,b*32,bar_x+8*b); }
    sts32(ct+14*4, 0x3f800000u);
  }
  __syncthreads();

  if (warp < 8){
    asm volatile("setmaxnreg.inc.sync.aligned.u32 192;");
    const int w = warp, wg = w>>2;
    uint32_t A[2][18][4];
    {
      #pragma unroll
      for (int m=0;m<2;m++){
        const bf16* W = (j==0?Wq:(j==1?Wk:Wv)) + h*128 + 16*(m==0 ? (w^4) : w) + 4*t + (size_t)(32*wg+g)*4096;
        #pragma unroll
        for (int k=0;k<18;k++){
          const int row = 64*(k>>1) + 16*(k&1);
          uint2 lo = __ldg((const uint2*)(W + (size_t)row*4096));
          uint2 hi = __ldg((const uint2*)(W + (size_t)(row+8)*4096));
          A[m][k][0]=lo.x; A[m][k][1]=lo.y; A[m][k][2]=hi.x; A[m][k][3]=hi.y;
        }
      }
      #pragma unroll
      for (int m=0;m<2;m++)
      #pragma unroll
      for (int k=0;k<18;k++){ A[m][k][0]=movm(A[m][k][0]); A[m][k][1]=movm(A[m][k][1]); A[m][k][2]=movm(A[m][k][2]); A[m][k][3]=movm(A[m][k][3]); }
      if (j==2){
        float mxn=0.f;
        #pragma unroll
        for (int m=0;m<2;m++){
          float s0=0.f,s1=0.f;
          #pragma unroll
          for (int k=0;k<18;k++){
            s0 += fabsf(bf_lo(A[m][k][0]))+fabsf(bf_hi(A[m][k][0]))+fabsf(bf_lo(A[m][k][2]))+fabsf(bf_hi(A[m][k][2]));
            s1 += fabsf(bf_lo(A[m][k][1]))+fabsf(bf_hi(A[m][k][1]))+fabsf(bf_lo(A[m][k][3]))+fabsf(bf_hi(A[m][k][3]));
          }
          s0 += __shfl_xor_sync(~0u,s0,1); s0 += __shfl_xor_sync(~0u,s0,2);
          s1 += __shfl_xor_sync(~0u,s1,1); s1 += __shfl_xor_sync(~0u,s1,2);
          mxn = fmaxf(mxn,fmaxf(s0,s1));
        }
        unsigned r = __reduce_max_sync(~0u, __float_as_uint(mxn));
        if (lane==0) sts32(ct+(24+w)*4, r);
      }
      bar_arrive(4,384);
    }
    uint4* gx = (j==0?g_qx:(j==1?g_kx:g_vx)) + (size_t)h*512 + (j<2 ? w*32 : w*64) + lane;
    const uint32_t slot = sb + SM_Q + j*2048 + (w*32+lane)*8;
    const uint32_t r1d = mapa(slot,(j+1)%3), r2d = mapa(slot,(j+2)%3);
    const uint32_t lda = sb + SM_MEM + (lane&7)*1168 + (lane>>3)*16 + wg*64;
    const uint32_t xr = sb + SM_XR + w*2048 + lane*16;
    const int xd = wg ? -8192 : 8192;
    uint2* gm = (j==1?g_km:g_vm) + h*256 + w*32 + lane;
    int xb = 0, xph = 0;
    for (int s=-3;s<NSEG;s++){
      if (s>=0){
        float c[2][2][4];
        #pragma unroll
        for (int q=0;q<4;q++){ c[q>>1][q&1][0]=c[q>>1][q&1][1]=c[q>>1][q&1][2]=c[q>>1][q&1][3]=0.f; }
        #pragma unroll
        for (int ch=0;ch<3;ch++){
          bar_sync(1+ch,384);
          uint32_t b[6][2];
          #pragma unroll
          for (int q=0;q<3;q++) ldsm4(b[2*q][0],b[2*q][1],b[2*q+1][0],b[2*q+1][1], lda + (ch*3+q)*128);
          if (w==0 && ch==0) TSD(0,b[0][0]);
          if (w==0 && ch==2) TSD(1,b[0][0]);
          if (ch<2){
            #pragma unroll
            for (int q=0;q<6;q++){ const int k=ch*6+q;
              mma16816(c[0][q&1], A[0][k][0],A[0][k][1],A[0][k][2],A[0][k][3], b[q][0],b[q][1]);
              mma16816(c[1][q&1], A[1][k][0],A[1][k][1],A[1][k][2],A[1][k][3], b[q][0],b[q][1]); }
          } else {
            #pragma unroll
            for (int q=0;q<6;q++){ const int k=ch*6+q; mma16816(c[0][q&1], A[0][k][0],A[0][k][1],A[0][k][2],A[0][k][3], b[q][0],b[q][1]); }
            #pragma unroll
            for (int q=0;q<6;q++){ const int k=ch*6+q; mma16816(c[1][q&1], A[1][k][0],A[1][k][1],A[1][k][2],A[1][k][3], b[q][0],b[q][1]); }
          }
        }
        sts128f(xr + xd, c[0][0][0]+c[0][1][0], c[0][0][1]+c[0][1][1], c[0][0][2]+c[0][1][2], c[0][0][3]+c[0][1][3]);
        const float us = F(lds32(ct+14*4));
        bar_sync(9+(w&3),64);
        uint4 o = lds128(xr);
        uint32_t p0 = pack2(((c[1][0][0]+c[1][1][0])+F(o.x))*us, ((c[1][0][1]+c[1][1][1])+F(o.y))*us);
        uint32_t p1 = pack2(((c[1][0][2]+c[1][1][2])+F(o.z))*us, ((c[1][0][3]+c[1][1][3])+F(o.w))*us);
        if (j<2){ p0=movm(p0); p1=movm(p1); }
        if (s<NSEG-1){
          asm volatile("st.async.shared::cluster.mbarrier::complete_tx::bytes.v2.b32 [%0], {%1,%2}, [%3];"::"r"(r1d),"r"(p0),"r"(p1),"r"(r1d-slot+bar_qkv):"memory");
          asm volatile("st.async.shared::cluster.mbarrier::complete_tx::bytes.v2.b32 [%0], {%1,%2}, [%3];"::"r"(r2d),"r"(p0),"r"(p1),"r"(r2d-slot+bar_qkv):"memory");
          asm volatile("st.shared.v2.b32 [%0],{%1,%2};"::"r"(slot),"r"(p0),"r"(p1):"memory");
          __syncwarp();
          if (lane==0) mbar_arrive(bar_qkv);
        }
        if (w==0) TSD(2,p0);
        if (j>=1) *gm = make_uint2(p0,p1);
        gm += NH*256;
        asm volatile("fence.acq_rel.gpu;":::"memory");
        __syncwarp();
        if (lane==0) asm volatile("red.relaxed.gpu.global.add.u32 [%0],1;"::"l"(g_segflag+s*32):"memory");
        if (tid==32 && s+1<NSEG-1){ uint32_t bb=((s+1)&1); const uint4* src=g_kx+(size_t)((DOX?(s+1):((s+1)%3))*NH+h)*512; mbar_expect(bar_kv+8*bb,16384); bulk_g2s(sb+SM_KV+bb*16384,src,8192,bar_kv+8*bb); bulk_g2s(sb+SM_KV+bb*16384+8192,src+(g_vx-g_kx),8192,bar_kv+8*bb); }
        if (tid==0 && s+4<NSEG && DOX){ int pb = xb==NXB-1?0:xb+1; mbar_expect(bar_x+8*pb, XBUF); for (int q=3*j;q<3*j+3;q++) tma_load_2d_mc(sb+SM_X+pb*XBUF+q*4096,&tmx,q*64,(s+4)*32,bar_x+8*pb,7); }
        if (s<NSEG-1) bar_sync(7,384);
      }
      if (s+3<NSEG && (DOX || s<0)){
        mbar_wait(bar_x+8*xb, xph);
        float d[16];
        uint64_t desc = ((uint64_t)(((sb+SM_X+xb*XBUF+wg*64)&0x3FFFF)>>4)) | ((uint64_t)1<<16) | ((uint64_t)(1024>>4)<<32) | ((uint64_t)1<<62);
        asm volatile("wgmma.fence.sync.aligned;":::"memory");
        #pragma unroll
        for (int k=0;k<18;k++) wgmma_rs_n32(d, A[0][k][0],A[0][k][1],A[0][k][2],A[0][k][3], desc + (uint64_t)(((k>>1)*4096 + (k&1)*32)>>4), k>0);
        asm volatile("wgmma.commit_group.sync.aligned;":::"memory");
        asm volatile("wgmma.wait_group.sync.aligned 0;":::"memory");
        #pragma unroll
        for (int n=0;n<4;n++) sts128f(xr+xd+n*512, d[4*n],d[4*n+1],d[4*n+2],d[4*n+3]);
        asm volatile("wgmma.fence.sync.aligned;":::"memory");
        #pragma unroll
        for (int k=0;k<18;k++) wgmma_rs_n32(d, A[1][k][0],A[1][k][1],A[1][k][2],A[1][k][3], desc + (uint64_t)(((k>>1)*4096 + (k&1)*32)>>4), k>0);
        asm volatile("wgmma.commit_group.sync.aligned;":::"memory");
        bar_sync(9+(w&3),64);
        asm volatile("wgmma.wait_group.sync.aligned 0;":::"memory");
        uint32_t p[8];
        #pragma unroll
        for (int n=0;n<4;n++){ uint4 o=lds128(xr+n*512); p[2*n]=pack2(d[4*n]+F(o.x),d[4*n+1]+F(o.y)); p[2*n+1]=pack2(d[4*n+2]+F(o.z),d[4*n+3]+F(o.w)); }
        if (j<2){
          #pragma unroll
          for (int n=0;n<8;n++) p[n]=movm(p[n]);
          gx[0] = make_uint4(p[0],p[2],p[1],p[3]);
          gx[256] = make_uint4(p[4],p[6],p[5],p[7]);
        } else {
          gx[0] = make_uint4(p[0],p[1],p[2],p[3]);
          gx[32] = make_uint4(p[4],p[5],p[6],p[7]);
        }
        gx += NH*512;
        if (s>=0 && w==0) TSD(10,p[0]);
        if (s<0){
          bar_sync(8,256);
          if (tid==0 && s==-3){ mbar_expect(bar_x, XBUF); for (int q=0;q<9;q++) tma_load_2d(sb+SM_X+q*4096,&tmx,q*64,3*32,bar_x); }
        }
        if (++xb==NXB){ xb=0; xph^=1; }
      }
      if (s==-1){ __threadfence(); asm volatile("barrier.cluster.arrive.release.aligned;\nbarrier.cluster.wait.acquire.aligned;":::"memory"); }
    }
    asm volatile("barrier.cluster.arrive.release.aligned;\nbarrier.cluster.wait.acquire.aligned;":::"memory");
  } else {
    asm volatile("setmaxnreg.dec.sync.aligned.u32 120;");
    const int a = warp-8;
    {
      unsigned gen0 = 0;
      if (lane==0) gen0 = *(volatile unsigned*)&g_bar_gen;
      unsigned* gn = g_norm + (gen0&1)*96;
      for (int i=tid-256;i<512;i+=128) g_acc[blockIdx.x*512+i] = make_uint4(0,0,0,0);
      if (blockIdx.x==0){ for (int i=tid-256;i<NSEG*32;i+=128){ g_tmax[i]=0; g_segflag[i]=0; } for (int i=tid-256;i<192;i+=128) g_cnt[i*32]=0; if (tid==256) g_tbase=gtime(); __threadfence(); bar_sync(5,128); }
      asm volatile("griddepcontrol.launch_dependents;":::"memory");
      const bf16* W = Wo + (size_t)h*128*DM + 192*j + 48*a + 4*t;
      const int er = 4*(g>>1) + (g&1);
      float mxn=0.f;
      #pragma unroll
      for (int X=0;X<3;X++){
        float s0=0.f,s1=0.f;
        #pragma unroll
        for (int k=0;k<8;k++){
          uint2 lo = __ldg((const uint2*)(W + (size_t)(16*k+er)*DM + 16*X));
          uint2 hi = __ldg((const uint2*)(W + (size_t)(16*k+er+2)*DM + 16*X));
          uint32_t r0=movm(__byte_perm(lo.x,lo.y,0x5410)), r1=movm(__byte_perm(lo.x,lo.y,0x7632)), r2=movm(__byte_perm(hi.x,hi.y,0x5410)), r3=movm(__byte_perm(hi.x,hi.y,0x7632));
          *(uint4*)(sm + SM_WO + (((a*3+X)*8+k)*32+lane)*16) = make_uint4(r0,r1,r2,r3);
          s0 += fabsf(bf_lo(r0))+fabsf(bf_hi(r0))+fabsf(bf_lo(r2))+fabsf(bf_hi(r2));
          s1 += fabsf(bf_lo(r1))+fabsf(bf_hi(r1))+fabsf(bf_lo(r3))+fabsf(bf_hi(r3));
        }
        s0 += __shfl_xor_sync(~0u,s0,1); s0 += __shfl_xor_sync(~0u,s0,2);
        s1 += __shfl_xor_sync(~0u,s1,1); s1 += __shfl_xor_sync(~0u,s1,2);
        mxn = fmaxf(mxn,fmaxf(s0,s1));
      }
      unsigned wo1 = __reduce_max_sync(~0u, __float_as_uint(mxn));
      unsigned xm=0, mm=0;
      for (int i=tid-256;i<1536;i+=128){ uint4 v=__ldg((const uint4*)x + blockIdx.x*1536 + i);
        xm=max(xm,max(max(max((v.x<<16)&0x7fffffffu,v.x&0x7fff0000u),max((v.y<<16)&0x7fffffffu,v.y&0x7fff0000u)),max(max((v.z<<16)&0x7fffffffu,v.z&0x7fff0000u),max((v.w<<16)&0x7fffffffu,v.w&0x7fff0000u)))); }
      for (int i=tid-256;i<8*72;i+=128){ int r=i/72, c8=i%72; uint4 v=__ldg((const uint4*)(mem0 + r*DM + c8*8)); *(uint4*)(sm+SM_MEM+r*1168+c8*16) = v;
        mm=max(mm,max(max(max((v.x<<16)&0x7fffffffu,v.x&0x7fff0000u),max((v.y<<16)&0x7fffffffu,v.y&0x7fff0000u)),max(max((v.z<<16)&0x7fffffffu,v.z&0x7fff0000u),max((v.w<<16)&0x7fffffffu,v.w&0x7fff0000u)))); }
      xm = __reduce_max_sync(~0u,xm); mm = __reduce_max_sync(~0u,mm);
      bar_sync(4,384);
      if (lane==0){
        sts32(ct+(20+a)*4, mm);
        atomicMax(gn, xm); atomicMax(gn+64, wo1);
        if (j==2){ atomicMax(gn+32, max(lds32(ct+(24+2*a)*4), lds32(ct+(25+2*a)*4))); }
      }
      __threadfence();
      bar_sync(5,128);
      if (tid==256){ unsigned old = atomicInc(&g_bar_cnt, 95); if (old==95){ __threadfence(); atomicAdd(&g_bar_gen,1);} int it=0; while (*(volatile unsigned*)&g_bar_gen == gen0 && ++it<(1<<24)); __threadfence();
        unsigned tb=*(volatile unsigned*)&g_tbase;
        sts32(ct,tb); sts32(ct+4,tb); sts32(ct+8,tb); sts32(ct+12,1800); sts32(ct+16,0); sts32(ct+20,0); sts32(ct+28,tb); sts32(ct+32,g_pK); sts32(ct+36,g_pE); sts32(ct+40,g_pD); sts32(ct+44,tb); sts32(ct+48,0); sts32(ct+52,0);
        float cw = 2.f*F(*(volatile unsigned*)(gn+32)) * 32.f*F(*(volatile unsigned*)(gn+64)) * 1.1f;
        sts32(ct+60,__float_as_uint(cw)); sts32(ct+64,*(volatile unsigned*)gn);
        if (blockIdx.x==0){ unsigned* go = g_norm + ((gen0&1)^1)*96; go[0]=0; go[32]=0; go[64]=0; }
      }
    }
    asm volatile("barrier.cluster.arrive.release.aligned;\nbarrier.cluster.wait.acquire.aligned;":::"memory");
    const float cexp = 0.08838834764831845f*1.4426950408889634f;
    const uint32_t sts_mem = sb + SM_MEM + (2*t)*1168 + (48*a + 2*g)*2;
    const int q0=2*t, q1=2*t+1;
    const uint32_t wpos = a<2 ? (16*a + 4*(g>>1)+(g&1)) : (32+g);
    const uint32_t sw0 = sb+SM_S+(q0*64+16*((q0^(q0>>1))&1) + wpos)*4, sw1 = sb+SM_S+(q1*64+16*((q1^(q1>>1))&1) + wpos)*4;
    const uint32_t srd = sb+SM_S+(g*64+16*((g^(g>>1))&1))*4;
    const uint32_t l16 = sb + lane*16, l8 = sb + lane*8;
    const uint32_t wof = l16 + SM_WO + a*3*4096;
    const uint32_t ost = sb+SM_O+(lane&7)*272+(lane>>3)*16;
    const uint32_t zr = lds32(ct+48);
    uint4* ap = g_acc + a*64 + lane;
    if (tid==256){ const uint4* gk = g_kx + (size_t)h*512; asm volatile("fence.proxy.async;":::"memory"); mbar_expect(bar_kv,16384); bulk_g2s(sb+SM_KV,gk,8192,bar_kv); bulk_g2s(sb+SM_KV+8192,gk+(g_vx-g_kx),8192,bar_kv); }
    unsigned tred = 0;
    float usc = 1.f;
    int retries=0;
    for (int s=0;s<NSEG;s++){
      uint4 kx[8], vx[4], Wf[3][8];
      #pragma unroll
      for (int k=0;k<5;k++) Wf[0][k] = lds128(wof + k*512);
      if (s>0){
        uint4 v[6];
        const uint4* ldp = ap - 768;
        unsigned bad = 1;
        { const unsigned G0=lds32(ct), tl = tred + lds32(ct+40);
          if ((int)(gtime()-G0)<0){ bad=0; while ((int)(gtime()-G0)<0); }
          else spin_until(tl); }
        #pragma unroll
        for (int q=0;q<6;q++) v[q] = ld_cg_v4(ldp + (q>>1)*256 + (q&1)*32);
        if (a==0) TS(3);
        uint32_t hm=0;
        #pragma unroll
        for (int jj=0;jj<3;jj++){
          int it=0;
          while (!__all_sync(~0u, v[2*jj].w==0x5000u && v[2*jj+1].w==0x5000u) && ++it<(1<<18)){
            retries++; bad=1;
            #pragma unroll
            for (int q=2*jj;q<6;q++) if (v[q].w!=0x5000u) v[q] = ld_cg_v4(ldp + (q>>1)*256 + (q&1)*32);
          }
          uint4 u=v[jj*2], r=v[jj*2+1];
          uint32_t ad = sts_mem + jj*384;
          sts32(ad,    h2bf(u.x)); sts32(ad+1168,    h2bf(u.y));
          sts32(ad+32, h2bf(u.z)); sts32(ad+1168+32, h2bf(r.x));
          sts32(ad+64, h2bf(r.y)); sts32(ad+1168+64, h2bf(r.z));
          bar_arrive(1+jj,384);
          if (a==0 && jj==0) TS(4);
        }
        if (a==3) TS(9);
        #pragma unroll
        for (int q=0;q<6;q++) hm = __vmaxu2(hm, __vmaxu2(__vmaxu2(v[q].x&0x7fff7fffu, v[q].y&0x7fff7fffu), v[q].z&0x7fff7fffu));
        hm = __reduce_max_sync(~0u, max(hm&0xffffu, hm>>16));
        if (lane==0){
          float hf; asm("{.reg .f16 a; mov.b16 a,%1; cvt.f32.f16 %0,a;}":"=f"(hf):"h"((unsigned short)hm));
          sts32(ct+(20+a)*4, __float_as_uint(hf*usc*1.01f));
          if (bad) asm volatile("st.relaxed.gpu.global.u32 [%0],%1;"::"l"(g_tmax + s*32+1),"r"(1):"memory");
        }
        if (tid==256+96){
          unsigned M=0, MB=0;
          if (s>=2) asm volatile("ld.relaxed.gpu.global.v2.u32 {%0,%1},[%2];":"=r"(M),"=r"(MB):"l"(g_tmax + (s-2)*32):"memory");
          unsigned Gn, G0=lds32(ct), P=lds32(ct+12), K=lds32(ct+32), tb=lds32(ct+28), Mp=lds32(ct+52);
          sts32(ct+52,M);
          if (M==0 || Mp==0) Gn=tb;
          else if (MB){ unsigned Pf=min(max(M-Mp,P),4000u); unsigned c1=G0+P, c2=M+tb+K+2*Pf+lds32(ct+36); Gn = (int)(c2-c1)>0 ? c2 : c1; }
          else { unsigned Lc=lds32(ct+20), Lb=lds32(ct+16), La=M+tb-lds32(ct+8); sts32(ct+20,Lb); sts32(ct+16,La); P = max(max(La,Lb),Lc)+K; sts32(ct+12,P); Gn=G0+P; }
          sts32(ct+8,lds32(ct+4)); sts32(ct+4,G0); sts32(ct+44,Gn);
        }
      } else { bar_arrive(1,384); bar_arrive(2,384); bar_arrive(3,384); }
      if (s==NSEG-1) break;
      if (tid==256) mbar_expect(bar_qkv, 4096);
      mbar_wait(bar_kv+8*(s&1), (s>>1)&1);
      {
        const uint32_t kb = l16 + SM_KV + (s&1)*16384;
        #pragma unroll
        for (int q=0;q<8;q++) kx[q]=lds128(kb + ((a&1)*8+q)*512);
        #pragma unroll
        for (int q=0;q<4;q++) vx[q]=lds128(kb + 8192 + (a*4+q)*512);
      }
      mbar_wait(bar_qkv, s&1);
      uint2 qf[8];
      #pragma unroll
      for (int q=0;q<8;q++) qf[q] = lds64(l8+SM_Q+q*256);
      if (a>=2){
        #pragma unroll
        for (int q=0;q<8;q++){ uint2 kf = lds64(l8+SM_Q+2048+q*256); kx[q].x=kf.x; kx[q].z=kf.y; }
      }
      if (a==0) TSD(5,qf[0].x);
      {
        float s0[4]={0,0,0,0}, s1[4]={0,0,0,0}, s2[4]={0,0,0,0}, s3[4]={0,0,0,0};
        mma16816(s0, kx[0].x,kx[0].y,kx[0].z,kx[0].w, qf[0].x,qf[0].y);
        mma16816(s1, kx[1].x,kx[1].y,kx[1].z,kx[1].w, qf[1].x,qf[1].y);
        mma16816(s2, kx[2].x,kx[2].y,kx[2].z,kx[2].w, qf[2].x,qf[2].y);
        mma16816(s3, kx[3].x,kx[3].y,kx[3].z,kx[3].w, qf[3].x,qf[3].y);
        mma16816(s0, kx[4].x,kx[4].y,kx[4].z,kx[4].w, qf[4].x,qf[4].y);
        mma16816(s1, kx[5].x,kx[5].y,kx[5].z,kx[5].w, qf[5].x,qf[5].y);
        mma16816(s2, kx[6].x,kx[6].y,kx[6].z,kx[6].w, qf[6].x,qf[6].y);
        mma16816(s3, kx[7].x,kx[7].y,kx[7].z,kx[7].w, qf[7].x,qf[7].y);
        stsf(sw0, (s0[0]+s1[0])+(s2[0]+s3[0])); stsf(sw1, (s0[1]+s1[1])+(s2[1]+s3[1]));
        if (a<2){ stsf(sw0+8, (s0[2]+s1[2])+(s2[2]+s3[2])); stsf(sw1+8, (s0[3]+s1[3])+(s2[3]+s3[3])); }
      }
      uint2 vf0 = lds64(l8+SM_Q+4096+(2*a)*256), vf1 = lds64(l8+SM_Q+4096+(2*a+1)*256);
      bar_sync(5,128);
      uint4 r0=lds128(srd+t*16), r1=lds128(srd+64+t*16); uint2 r2=lds64(srd+128+t*8);
      if (a==0) TSD(6,r0.x);
      float sc[10]={F(r0.x),F(r0.y),F(r0.z),F(r0.w),F(r1.x),F(r1.y),F(r1.z),F(r1.w),F(r2.x),F(r2.y)};
      float mx = fmaxf(fmaxf(fmaxf(sc[0],sc[1]),fmaxf(sc[2],sc[3])),fmaxf(fmaxf(sc[4],sc[5]),fmaxf(sc[6],sc[7])));
      mx = fmaxf(mx,fmaxf(sc[8],sc[9]));
      { float m1=__shfl_xor_sync(~0u,mx,1), m2=__shfl_xor_sync(~0u,mx,2), m3=__shfl_xor_sync(~0u,mx,3); mx=fmaxf(fmaxf(mx,m1),fmaxf(m2,m3)); }
      {
        const uint32_t wp = wof | (__float_as_uint(mx) & zr);
        #pragma unroll
        for (int k=5;k<8;k++) Wf[0][k] = lds128(wp + k*512);
        #pragma unroll
        for (int k=0;k<5;k++) Wf[1][k] = lds128(wp + 4096 + k*512);
      }
      float mo = mx*cexp;
      #pragma unroll
      for (int q=0;q<10;q++) sc[q]=ex2(fmaf(sc[q],cexp,-mo));
      uint32_t P0a=pack2(sc[0],sc[1]), P0b=pack2(sc[2],sc[3]), P1a=pack2(sc[4],sc[5]), P1b=pack2(sc[6],sc[7]), Pm=pack2(sc[8],sc[9]);
      float o0[4]={0,0,0,0}, o1[4]={0,0,0,0};
      mma16816(o0, vx[0].x,vx[0].y,vx[0].z,vx[0].w, P0a,P0b);
      mma16816(o1, vx[2].x,vx[2].y,vx[2].z,vx[2].w, P0a,P0b);
      mma16816(o0, vx[1].x,vx[1].y,vx[1].z,vx[1].w, P1a,P1b);
      mma16816(o1, vx[3].x,vx[3].y,vx[3].z,vx[3].w, P1a,P1b);
      mma1688(o0, vf0.x,vf0.y, Pm);
      mma1688(o1, vf1.x,vf1.y, Pm);
      float sum = ((bf_lo(P0a)+bf_hi(P0a))+(bf_lo(P0b)+bf_hi(P0b)))+((bf_lo(P1a)+bf_hi(P1a))+(bf_lo(P1b)+bf_hi(P1b)))+(bf_lo(Pm)+bf_hi(Pm));
      uint32_t e0=pack2(o0[0],o0[1]), e1=pack2(o0[2],o0[3]);
      uint32_t e2=pack2(o1[0],o1[1]), e3=pack2(o1[2],o1[3]);
      asm volatile("stmatrix.sync.aligned.m8n8.x4.trans.shared.b16 [%0],{%1,%2,%3,%4};"::"r"(ost+64*a),"r"(e0),"r"(e1),"r"(e2),"r"(e3):"memory");
      bar_sync(6,128);
      uint32_t ob[8][2];
      #pragma unroll
      for (int q=0;q<4;q++) ldsm4(ob[2*q][0],ob[2*q][1],ob[2*q+1][0],ob[2*q+1][1], ost+q*64);
      #pragma unroll
      for (int k=5;k<8;k++) Wf[1][k] = lds128(wof + 4096 + k*512);
      if (a==0) TSD(7,ob[0][0]);
      float scl;
      { uint4 hq = lds128(ct+80); float hmx = fmaxf(fmaxf(fmaxf(F(hq.x),F(hq.y)),fmaxf(F(hq.z),F(hq.w))),F(lds32(ct+64)));
        float B = hmx*F(lds32(ct+60)); int eb = (int)((__float_as_uint(B)>>23)&0xff); int es = 127+14+127-eb; es = min(max(es,27),227);
        scl = F((unsigned)es<<23); usc = F((unsigned)(254-es)<<23); }
      sum += __shfl_xor_sync(~0u,sum,1);
      sum += __shfl_xor_sync(~0u,sum,2);
      const float i0 = rcpa(__shfl_sync(~0u,sum,8*t))*scl, i1 = rcpa(__shfl_sync(~0u,sum,8*t+4))*scl;
      uint4* rdp = ap + j*256;
      float C[3][2][4];
      #pragma unroll
      for (int X=0;X<3;X++)
      #pragma unroll
      for (int q=0;q<2;q++){ C[X][q][0]=C[X][q][1]=C[X][q][2]=C[X][q][3]=0.f; }
      #pragma unroll
      for (int k=0;k<8;k++){
        mma16816(C[0][k&1], Wf[0][k].x,Wf[0][k].y,Wf[0][k].z,Wf[0][k].w, ob[k][0],ob[k][1]);
        mma16816(C[1][k&1], Wf[1][k].x,Wf[1][k].y,Wf[1][k].z,Wf[1][k].w, ob[k][0],ob[k][1]);
        Wf[2][k] = lds128(wof + 8192 + k*512);
      }
      #pragma unroll
      for (int k=0;k<8;k++) mma16816(C[2][k&1], Wf[2][k].x,Wf[2][k].y,Wf[2][k].z,Wf[2][k].w, ob[k][0],ob[k][1]);
      red_h4(rdp, packh((C[0][0][0]+C[0][1][0])*i0,(C[0][0][2]+C[0][1][2])*i0), packh((C[0][0][1]+C[0][1][1])*i1,(C[0][0][3]+C[0][1][3])*i1),
                  packh((C[1][0][0]+C[1][1][0])*i0,(C[1][0][2]+C[1][1][2])*i0), 0x3C00u);
      red_h4(rdp+32, packh((C[1][0][1]+C[1][1][1])*i1,(C[1][0][3]+C[1][1][3])*i1), packh((C[2][0][0]+C[2][1][0])*i0,(C[2][0][2]+C[2][1][2])*i0),
                  packh((C[2][0][1]+C[2][1][1])*i1,(C[2][0][3]+C[2][1][3])*i1), 0x3C00u);
      asm volatile("mov.u32 %0, %%clock;":"=r"(tred)::"memory");
      if (tid==256+96){ asm volatile("red.relaxed.gpu.global.max.u32 [%0],%1;"::"l"(g_tmax + s*32),"r"(gtime()-lds32(ct+28)):"memory");
        sts32(ct, lds32(ct+44)); sts32(ct+56, __float_as_uint(usc));
      }
      ap += 768;
      if (a==0) TS(8);
      bar_arrive(7,384);
      bar_sync(5,128);
    }
    asm volatile("barrier.cluster.arrive.release.aligned;\nbarrier.cluster.wait.acquire.aligned;":::"memory");
  }
}
__device__ __forceinline__ unsigned ld_acq(const unsigned* p){ unsigned v; asm volatile("ld.acquire.gpu.global.u32 %0,[%1];":"=r"(v):"l"(p):"memory"); return v; }
__device__ __forceinline__ void wait_cnt(const unsigned* p, unsigned target){ int it=0; while (ld_acq(p) < target && ++it<(1<<22)) __nanosleep(100); }
__device__ __forceinline__ void signal_cnt(unsigned* p){ asm volatile("red.release.gpu.global.add.u32 [%0],1;"::"l"(p):"memory"); }
__device__ __forceinline__ void ldsm4t(uint32_t& r0,uint32_t& r1,uint32_t& r2,uint32_t& r3,uint32_t addr){
  asm volatile("ldmatrix.sync.aligned.m8n8.x4.trans.shared.b16 {%0,%1,%2,%3},[%4];":"=r"(r0),"=r"(r1),"=r"(r2),"=r"(r3):"r"(addr):"memory");
}
__device__ __forceinline__ void ldsm2t(uint32_t& r0,uint32_t& r1,uint32_t addr){
  asm volatile("ldmatrix.sync.aligned.m8n8.x2.trans.shared.b16 {%0,%1},[%2];":"=r"(r0),"=r"(r1):"r"(addr):"memory");
}
#define R8(d,o) "+f"(d[o]),"+f"(d[o+1]),"+f"(d[o+2]),"+f"(d[o+3]),"+f"(d[o+4]),"+f"(d[o+5]),"+f"(d[o+6]),"+f"(d[o+7])
__device__ __forceinline__ void wgmma_ss_n192(float* d, uint64_t da, uint64_t db, int scale_d){
  asm volatile("{.reg .pred p; setp.ne.b32 p, %98, 0;\n"
   "wgmma.mma_async.sync.aligned.m64n192k16.f32.bf16.bf16 {%0,%1,%2,%3,%4,%5,%6,%7,%8,%9,%10,%11,%12,%13,%14,%15,%16,%17,%18,%19,%20,%21,%22,%23,%24,%25,%26,%27,%28,%29,%30,%31,%32,%33,%34,%35,%36,%37,%38,%39,%40,%41,%42,%43,%44,%45,%46,%47,"
   "%48,%49,%50,%51,%52,%53,%54,%55,%56,%57,%58,%59,%60,%61,%62,%63,%64,%65,%66,%67,%68,%69,%70,%71,%72,%73,%74,%75,%76,%77,%78,%79,%80,%81,%82,%83,%84,%85,%86,%87,%88,%89,%90,%91,%92,%93,%94,%95}, %96, %97, p, 1, 1, 0, 1;}"
   : R8(d,0),R8(d,8),R8(d,16),R8(d,24),R8(d,32),R8(d,40),R8(d,48),R8(d,56),R8(d,64),R8(d,72),R8(d,80),R8(d,88)
   : "l"(da),"l"(db),"r"(scale_d));
}
__device__ __forceinline__ void wgmma_ss_n96(float* d, uint64_t da, uint64_t db, int scale_d){
  asm volatile("{.reg .pred p; setp.ne.b32 p, %50, 0;\n"
   "wgmma.mma_async.sync.aligned.m64n96k16.f32.bf16.bf16 {%0,%1,%2,%3,%4,%5,%6,%7,%8,%9,%10,%11,%12,%13,%14,%15,%16,%17,%18,%19,%20,%21,%22,%23,%24,%25,%26,%27,%28,%29,%30,%31,%32,%33,%34,%35,%36,%37,%38,%39,%40,%41,%42,%43,%44,%45,%46,%47}, %48, %49, p, 1, 1, 0, 1;}"
   : R8(d,0),R8(d,8),R8(d,16),R8(d,24),R8(d,32),R8(d,40)
   : "l"(da),"l"(db),"r"(scale_d));
}

struct AuxMaps { CUtensorMap x128, ao, wo, wob, wqkv; };

__device__ __forceinline__ void gemm_issue(uint32_t sb, int st, const CUtensorMap* tmA, const CUtensorMap* tmB0, const CUtensorMap* tmB1, int kbs, int kb, int row0, int col0){
  uint32_t full = sb + A_BAR + st*8, dst = sb + st*A_STAGE;
  mbar_expect(full, A_STAGE);
  tma_load_2d(dst, tmA, kb*64, row0, full);
  const CUtensorMap* tb = kb<kbs ? tmB0 : tmB1; int kr = (kb<kbs ? kb : kb-kbs)*64;
  #pragma unroll
  for (int q=0;q<5;q++) tma_load_2d(dst+16384+q*8192, tb, col0+q*64, kr, full);
}
__device__ __forceinline__ void gemm_main(float* acc, uint32_t sb, unsigned& itc, const CUtensorMap* tmA, const CUtensorMap* tmB0, const CUtensorMap* tmB1, int kbs, int kb0, int kb1, int row0, int col0){
  const int tid=threadIdx.x, wg=tid>>7, nk=kb1-kb0;
  #pragma unroll
  for (int i=0;i<144;i++) acc[i]=0.f;
  if (tid==0){ asm volatile("fence.proxy.async;":::"memory"); for (int i=0;i<A_NST && i<nk;i++) gemm_issue(sb,(itc+i)%A_NST,tmA,tmB0,tmB1,kbs,kb0+i,row0,col0); }
  for (int i=0;i<nk;i++){
    const unsigned it=itc+i; const int st=it%A_NST;
    mbar_wait(sb+A_BAR+st*8, (it/A_NST)&1);
    uint64_t da = ((uint64_t)(((sb+st*A_STAGE+wg*8192)&0x3FFFF)>>4)) | ((uint64_t)1<<16) | ((uint64_t)(1024>>4)<<32) | ((uint64_t)1<<62);
    uint64_t db = ((uint64_t)(((sb+st*A_STAGE+16384)&0x3FFFF)>>4)) | ((uint64_t)(8192>>4)<<16) | ((uint64_t)(1024>>4)<<32) | ((uint64_t)1<<62);
    asm volatile("wgmma.fence.sync.aligned;":::"memory");
    #pragma unroll
    for (int k=0;k<4;k++){
      wgmma_ss_n192(acc, da+k*2, db+k*128, (i|k)!=0);
      wgmma_ss_n96(acc+96, da+k*2, db+k*128+(3*8192>>4), (i|k)!=0);
    }
    asm volatile("wgmma.commit_group.sync.aligned;":::"memory");
    if (i>0){
      asm volatile("wgmma.wait_group.sync.aligned 1;":::"memory");
      const unsigned pit=it-1; const int ps=pit%A_NST;
      if ((tid&31)==0) mbar_arrive(sb+A_BAR+32+ps*8);
      if (tid==0 && i-1+A_NST<nk){ mbar_wait(sb+A_BAR+32+ps*8,(pit/A_NST)&1); gemm_issue(sb,ps,tmA,tmB0,tmB1,kbs,kb0+i-1+A_NST,row0,col0); }
      __syncwarp();
    }
  }
  asm volatile("wgmma.wait_group.sync.aligned 0;":::"memory");
  if ((tid&31)==0) mbar_arrive(sb+A_BAR+32+((itc+nk-1)%A_NST)*8);
  itc += nk;
}

__global__ void __launch_bounds__(256,1)
aux_kernel(const __grid_constant__ AuxMaps tm, const bf16* __restrict__ x, const bf16* __restrict__ gate_w, bf16* __restrict__ out)
{
  extern __shared__ __align__(1024) unsigned char sm[];
  const uint32_t sb = smem_u32(sm);
  const int tid=threadIdx.x, lane=tid&31, w=tid>>5, g=lane>>2, t=lane&3;
  volatile unsigned* sh = (volatile unsigned*)(sm + A_BAR + 128);
  const uint32_t bar_b = sb + A_BAR + 64;
  if (tid==0){ for (int i=0;i<A_NST;i++){ mbar_init(sb+A_BAR+i*8,1); mbar_init(sb+A_BAR+32+i*8,8);} mbar_init(bar_b,1); mbar_init(bar_b+8,1); asm volatile("fence.mbarrier_init.release.cluster;":::"memory"); }
  unsigned itc=0, bph=0;
  unsigned nxt = 0;
  if (tid==0) nxt = atomicAdd(&g_cnt[C_TASK],1);
  while (true){
    __syncthreads();
    if (tid==0){ sh[0]=nxt; nxt = atomicAdd(&g_cnt[C_TASK],1); }
    __syncthreads();
    const int task = sh[0];
    if (task>=T_TOTAL) break;
    if (task < T0_BQ){
      for (int r=w; r<128; r+=8){
        const int row=task*128+r; float s=0.f;
        for (int c=lane;c<72;c+=32){ uint4 a=__ldg((const uint4*)(x+(size_t)row*DM)+c), b=__ldg((const uint4*)gate_w+c);
          s += bf_lo(a.x)*bf_lo(b.x)+bf_hi(a.x)*bf_hi(b.x)+bf_lo(a.y)*bf_lo(b.y)+bf_hi(a.y)*bf_hi(b.y)+bf_lo(a.z)*bf_lo(b.z)+bf_hi(a.z)*bf_hi(b.z)+bf_lo(a.w)*bf_lo(b.w)+bf_hi(a.w)*bf_hi(b.w); }
        #pragma unroll
        for (int o=16;o;o>>=1) s+=__shfl_xor_sync(~0u,s,o);
        if (lane==0) g_gate[row]=1.f/(1.f+__expf(-s));
      }
      __syncthreads();
      if (tid==0){ __threadfence(); signal_cnt(&g_cnt[C_GATE*32]); }
    } else if (task < T0_BA){
      const int rb=(task-T0_BQ)/6, nt=(task-T0_BQ)%6;
      float acc[144];
      gemm_main(acc,sb,itc,&tm.x128,&tm.wqkv,&tm.wqkv,9,0,9,rb*128,nt*288);
      __syncthreads();
      const uint32_t padv = nt>=4 ? 0x00003F80u : 0u;
      for (int i=tid;i<2048;i+=256){ uint32_t ad=sb+i*48+36; sts32(ad,padv); sts32(ad+4,0); sts32(ad+8,0); }
      const int r0=16*w+g;
      #pragma unroll
      for (int jn=0;jn<36;jn++){
        const int n=8*jn+2*t; const int hl=(n*3641)>>16, d=n-hl*18;
        uint32_t ad = sb + hl*6144 + r0*48 + d*2;
        sts32(ad, pack2(acc[4*jn],acc[4*jn+1])); sts32(ad+8*48, pack2(acc[4*jn+2],acc[4*jn+3]));
      }
      asm volatile("fence.proxy.async;":::"memory");
      __syncthreads();
      if (tid<16){
        asm volatile("cp.async.bulk.global.shared::cta.bulk_group [%0],[%1],%2;"::"l"(g_bq+((size_t)(nt*16+tid)*SEQ+rb*128)*24),"r"(sb+tid*6144),"r"(6144):"memory");
        asm volatile("cp.async.bulk.commit_group;":::"memory");
        asm volatile("cp.async.bulk.wait_group 0;":::"memory");
        asm volatile("fence.proxy.async;":::"memory");
        __threadfence();
      }
      __syncwarp();
      if (tid==0) signal_cnt(&g_cnt[(C_BQ+rb)*32]);
    } else if (task < T0_RB){
      const int rb=(task-T0_BA)>>3, hq=(task-T0_BA)&7;
      const int kstart = rb*128-256, kskip = kstart<0 ? -kstart : 0;
      constexpr int BUF=6144+2*18432;
      if (tid==0){
        wait_cnt(&g_cnt[C_GATE*32],16);
        for (int r=max(rb-2,0);r<=rb;r++) wait_cnt(&g_cnt[(C_BQ+r)*32],6);
        asm volatile("fence.proxy.async;":::"memory");
        for (int i=0;i<2;i++){ const int hh=hq*4+i; uint32_t b=sb+i*BUF; uint32_t by=(384-kskip)*48;
          mbar_expect(bar_b+8*i, 6144+2*by);
          bulk_g2s(b, g_bq+((size_t)hh*SEQ+rb*128)*24, 6144, bar_b+8*i);
          bulk_g2s(b+6144+kskip*48, g_bq+((size_t)(32+hh)*SEQ+kstart+kskip)*24, by, bar_b+8*i);
          bulk_g2s(b+6144+18432+kskip*48, g_bq+((size_t)(64+hh)*SEQ+kstart+kskip)*24, by, bar_b+8*i); }
      }
      __syncthreads();
      const int q0=rb*128+16*w;
      const float g0=1.f-__ldcg(&g_gate[q0+g]), g1=1.f-__ldcg(&g_gate[q0+g+8]);
      const int imin = q0<256 ? (256-q0)>>4 : 0;
      const float ce = 0.23570226039551584f*1.4426950408889634f;
      for (int hi=0;hi<4;hi++){
        const uint32_t b=sb+(hi&1)*BUF;
        mbar_wait(bar_b+8*(hi&1), bph^(hi>>1));
        uint32_t qa[6];
        ldsm4(qa[0],qa[1],qa[2],qa[3], b + (16*w+(lane&15))*48 + (lane>>4)*16);
        ldsm2(qa[4],qa[5], b + (16*w+(lane&15))*48 + 32);
        float S[17][8];
        const uint32_t kb4 = b+6144+(16*w+(lane&7)+((lane>>4)<<3))*48+((lane>>3)&1)*16;
        const uint32_t kb2 = b+6144+(16*w+(lane&15))*48+32;
        #pragma unroll
        for (int i=0;i<17;i++){
          uint32_t k0,k1,k2,k3,k4,k5;
          ldsm4(k0,k1,k2,k3,kb4+i*768); ldsm2(k4,k5,kb2+i*768);
          #pragma unroll
          for (int e=0;e<8;e++) S[i][e]=0.f;
          mma16816(&S[i][0],qa[0],qa[1],qa[2],qa[3],k0,k1); mma1688(&S[i][0],qa[4],qa[5],k4);
          mma16816(&S[i][4],qa[0],qa[1],qa[2],qa[3],k2,k3); mma1688(&S[i][4],qa[4],qa[5],k5);
        }
        const float NEG=-INFINITY;
        #pragma unroll
        for (int e=0;e<8;e++){ const int c=(e>>2)*8+2*t+(e&1), r=g+((e>>1)&1)*8; if (!(c>r)) S[0][e]=NEG; if (!(c<=r)) S[16][e]=NEG; }
        if (imin>0){
          #pragma unroll
          for (int i=0;i<16;i++) if (i<imin){
            #pragma unroll
            for (int e=0;e<8;e++) S[i][e]=NEG; }
        }
        float m0=NEG,m1=NEG;
        #pragma unroll
        for (int i=0;i<17;i++){ m0=fmaxf(m0,fmaxf(fmaxf(S[i][0],S[i][1]),fmaxf(S[i][4],S[i][5]))); m1=fmaxf(m1,fmaxf(fmaxf(S[i][2],S[i][3]),fmaxf(S[i][6],S[i][7]))); }
        m0=fmaxf(m0,__shfl_xor_sync(~0u,m0,1)); m0=fmaxf(m0,__shfl_xor_sync(~0u,m0,2));
        m1=fmaxf(m1,__shfl_xor_sync(~0u,m1,1)); m1=fmaxf(m1,__shfl_xor_sync(~0u,m1,2));
        m0*=-ce; m1*=-ce;
        float o[3][4];
        #pragma unroll
        for (int c=0;c<3;c++){ o[c][0]=o[c][1]=o[c][2]=o[c][3]=0.f; }
        const uint32_t vb4 = b+6144+18432+(16*w+(lane&15))*48+(lane>>4)*16;
        const uint32_t vb2 = b+6144+18432+(16*w+(lane&15))*48+32;
        #pragma unroll
        for (int i=0;i<17;i++){
          if (i>=imin){
            uint32_t v0,v1,v2,v3,v4,v5;
            ldsm4t(v0,v1,v2,v3,vb4+i*768); ldsm2t(v4,v5,vb2+i*768);
            uint32_t p0=pack2(ex2(fmaf(S[i][0],ce,m0)),ex2(fmaf(S[i][1],ce,m0))), p1=pack2(ex2(fmaf(S[i][2],ce,m1)),ex2(fmaf(S[i][3],ce,m1)));
            uint32_t p2=pack2(ex2(fmaf(S[i][4],ce,m0)),ex2(fmaf(S[i][5],ce,m0))), p3=pack2(ex2(fmaf(S[i][6],ce,m1)),ex2(fmaf(S[i][7],ce,m1)));
            mma16816(o[0],p0,p1,p2,p3,v0,v1); mma16816(o[1],p0,p1,p2,p3,v2,v3); mma16816(o[2],p0,p1,p2,p3,v4,v5);
          }
        }
        const float s0=g0*rcpa(__shfl_sync(~0u,o[2][0],(lane&~3)|1)), s1=g1*rcpa(__shfl_sync(~0u,o[2][2],(lane&~3)|1));
        bf16* dst = g_ao + (size_t)(q0+g)*AOW + 4096 + (hq*4+hi)*18 + 2*t;
        *(uint32_t*)(dst) = pack2(o[0][0]*s0,o[0][1]*s0); *(uint32_t*)(dst+8) = pack2(o[1][0]*s0,o[1][1]*s0);
        *(uint32_t*)(dst+8*AOW) = pack2(o[0][2]*s1,o[0][3]*s1); *(uint32_t*)(dst+8*AOW+8) = pack2(o[1][2]*s1,o[1][3]*s1);
        if (t==0){ *(uint32_t*)(dst+16) = pack2(o[2][0]*s0,o[2][1]*s0); *(uint32_t*)(dst+8*AOW+16) = pack2(o[2][2]*s1,o[2][3]*s1); }
        if (hi<2){
          __syncthreads();
          if (tid==0){ const int hh=hq*4+hi+2; uint32_t by=(384-kskip)*48;
            mbar_expect(bar_b+8*hi, 6144+2*by);
            bulk_g2s(b, g_bq+((size_t)hh*SEQ+rb*128)*24, 6144, bar_b+8*hi);
            bulk_g2s(b+6144+kskip*48, g_bq+((size_t)(32+hh)*SEQ+kstart+kskip)*24, by, bar_b+8*hi);
            bulk_g2s(b+6144+18432+kskip*48, g_bq+((size_t)(64+hh)*SEQ+kstart+kskip)*24, by, bar_b+8*hi); }
        }
      }
      __syncthreads();
      if (tid==0){ __threadfence(); signal_cnt(&g_cnt[(C_BA+rb)*32]); }
    } else {
      int u = task - T0_RB, rb = u / T_RB, v = u % T_RB;
      if (rb>=15){ rb=15; v=u-15*T_RB; }
      if (v<16){
        const int seg=rb*4+(v>>2), hg=v&3, h=hg*8+w;
        if (tid==0){ wait_cnt(&g_cnt[C_GATE*32],16); wait_cnt(&g_segflag[seg*32], SEGFLAG_N); }
        __syncthreads();
        const size_t base=(size_t)(seg*NH+h);
        const uint4* pq=g_qx+base*512+lane; const uint4* pk=g_kx+base*512+lane; const uint4* pv=g_vx+base*512+lane;
        const uint2* pkm=g_km+base*256+lane; const uint2* pvm=g_vm+base*256+lane;
        float S0[3][4], S1[5][4];
        #pragma unroll
        for (int n=0;n<3;n++){ S0[n][0]=S0[n][1]=S0[n][2]=S0[n][3]=0.f; }
        #pragma unroll
        for (int n=0;n<5;n++){ S1[n][0]=S1[n][1]=S1[n][2]=S1[n][3]=0.f; }
        #pragma unroll
        for (int ks=0;ks<8;ks++){
          uint4 qa=__ldcg(pq+ks*32), qb=__ldcg(pq+256+ks*32), ka=__ldcg(pk+ks*32), kb=__ldcg(pk+256+ks*32); uint2 km=__ldcg(pkm+ks*32);
          mma16816(S0[0],qa.x,qa.y,qa.z,qa.w,km.x,km.y); mma16816(S0[1],qa.x,qa.y,qa.z,qa.w,ka.x,ka.z); mma16816(S0[2],qa.x,qa.y,qa.z,qa.w,ka.y,ka.w);
          mma16816(S1[0],qb.x,qb.y,qb.z,qb.w,km.x,km.y); mma16816(S1[1],qb.x,qb.y,qb.z,qb.w,ka.x,ka.z); mma16816(S1[2],qb.x,qb.y,qb.z,qb.w,ka.y,ka.w);
          mma16816(S1[3],qb.x,qb.y,qb.z,qb.w,kb.x,kb.z); mma16816(S1[4],qb.x,qb.y,qb.z,qb.w,kb.y,kb.w);
        }
        uint4 vv[16]; uint2 vm[8];
        #pragma unroll
        for (int q=0;q<16;q++) vv[q]=__ldcg(pv+q*32);
        #pragma unroll
        for (int q=0;q<8;q++) vm[q]=__ldcg(pvm+q*32);
        const float NEG=-INFINITY, ce=0.08838834764831845f*1.4426950408889634f;
        #pragma unroll
        for (int n=0;n<2;n++)
        #pragma unroll
        for (int e=0;e<4;e++){ const int c=n*8+2*t+(e&1), r=g+(e>>1)*8; if (c>r){ S0[1+n][e]=NEG; S1[3+n][e]=NEG; } }
        float ma=NEG,mb=NEG,mc=NEG,md=NEG;
        #pragma unroll
        for (int n=0;n<3;n++){ ma=fmaxf(ma,fmaxf(S0[n][0],S0[n][1])); mb=fmaxf(mb,fmaxf(S0[n][2],S0[n][3])); }
        #pragma unroll
        for (int n=0;n<5;n++){ mc=fmaxf(mc,fmaxf(S1[n][0],S1[n][1])); md=fmaxf(md,fmaxf(S1[n][2],S1[n][3])); }
        #pragma unroll
        for (int o=1;o<4;o<<=1){ ma=fmaxf(ma,__shfl_xor_sync(~0u,ma,o)); mb=fmaxf(mb,__shfl_xor_sync(~0u,mb,o)); mc=fmaxf(mc,__shfl_xor_sync(~0u,mc,o)); md=fmaxf(md,__shfl_xor_sync(~0u,md,o)); }
        ma*=-ce; mb*=-ce; mc*=-ce; md*=-ce;
        uint32_t P0[3][2], P1[5][2]; float sa=0,sbb=0,sc=0,sd=0;
        #pragma unroll
        for (int n=0;n<3;n++){ P0[n][0]=pack2(ex2(fmaf(S0[n][0],ce,ma)),ex2(fmaf(S0[n][1],ce,ma))); P0[n][1]=pack2(ex2(fmaf(S0[n][2],ce,mb)),ex2(fmaf(S0[n][3],ce,mb)));
          sa+=bf_lo(P0[n][0])+bf_hi(P0[n][0]); sbb+=bf_lo(P0[n][1])+bf_hi(P0[n][1]); }
        #pragma unroll
        for (int n=0;n<5;n++){ P1[n][0]=pack2(ex2(fmaf(S1[n][0],ce,mc)),ex2(fmaf(S1[n][1],ce,mc))); P1[n][1]=pack2(ex2(fmaf(S1[n][2],ce,md)),ex2(fmaf(S1[n][3],ce,md)));
          sc+=bf_lo(P1[n][0])+bf_hi(P1[n][0]); sd+=bf_lo(P1[n][1])+bf_hi(P1[n][1]); }
        #pragma unroll
        for (int o=1;o<4;o<<=1){ sa+=__shfl_xor_sync(~0u,sa,o); sbb+=__shfl_xor_sync(~0u,sbb,o); sc+=__shfl_xor_sync(~0u,sc,o); sd+=__shfl_xor_sync(~0u,sd,o); }
        const int row=seg*32+g;
        sa=__ldcg(&g_gate[row])*rcpa(sa); sbb=__ldcg(&g_gate[row+8])*rcpa(sbb); sc=__ldcg(&g_gate[row+16])*rcpa(sc); sd=__ldcg(&g_gate[row+24])*rcpa(sd);
        bf16* dst=g_ao+(size_t)row*AOW+h*128+4*t;
        #pragma unroll
        for (int mt=0;mt<8;mt++){
          float a0[4]={0,0,0,0},a1[4]={0,0,0,0},b0[4]={0,0,0,0},b1[4]={0,0,0,0};
          uint4 v0=vv[2*mt], v1=vv[2*mt+1];
          mma1688(a0,P0[0][0],P0[0][1],vm[mt].x); mma1688(a1,P0[0][0],P0[0][1],vm[mt].y);
          mma1688(b0,P1[0][0],P1[0][1],vm[mt].x); mma1688(b1,P1[0][0],P1[0][1],vm[mt].y);
          mma16816(a0,P0[1][0],P0[1][1],P0[2][0],P0[2][1],v0.x,v0.z); mma16816(a1,P0[1][0],P0[1][1],P0[2][0],P0[2][1],v0.y,v0.w);
          mma16816(b0,P1[1][0],P1[1][1],P1[2][0],P1[2][1],v0.x,v0.z); mma16816(b1,P1[1][0],P1[1][1],P1[2][0],P1[2][1],v0.y,v0.w);
          mma16816(b0,P1[3][0],P1[3][1],P1[4][0],P1[4][1],v1.x,v1.z); mma16816(b1,P1[3][0],P1[3][1],P1[4][0],P1[4][1],v1.y,v1.w);
          *(uint2*)(dst+16*mt)        = make_uint2(pack2(a0[0]*sa,a0[1]*sa),pack2(a1[0]*sa,a1[1]*sa));
          *(uint2*)(dst+8*AOW+16*mt)  = make_uint2(pack2(a0[2]*sbb,a0[3]*sbb),pack2(a1[2]*sbb,a1[3]*sbb));
          *(uint2*)(dst+16*AOW+16*mt) = make_uint2(pack2(b0[0]*sc,b0[1]*sc),pack2(b1[0]*sc,b1[1]*sc));
          *(uint2*)(dst+24*AOW+16*mt) = make_uint2(pack2(b0[2]*sd,b0[3]*sd),pack2(b1[2]*sd,b1[3]*sd));
        }
        __syncthreads();
        if (tid==0){ __threadfence(); signal_cnt(&g_cnt[(C_XA+rb*4+hg)*32]); }
      } else {
        v-=16;
        const int nt=v&1, sp=v>>1, tile=rb*2+nt;
        const int nsp = rb==15 ? 17 : 5;
        int kb0,kb1; bool whole=false, skip=false;
        if (rb<15){
          if (tid==0){
            unsigned want = (*(volatile unsigned*)&g_segflag[g_pWhole*32] == 0) ? (unsigned)(16+sp) : 1u;
            unsigned old = atomicCAS(&g_cnt[(C_MODE+tile)*32],0u,want);
            sh[1] = old ? old : want;
          }
          __syncthreads();
          const unsigned mode=sh[1];
          if (mode>=16){ if (mode==16+sp) whole=true; else skip=true; }
        }
        if (skip) continue;
        if (whole){ kb0=0; kb1=73; }
        else if (sp==0){ kb0=64; kb1=73; }
        else if (rb<15){ kb0=(sp-1)*16; kb1=kb0+16; }
        else { kb0=(sp-1)*4; kb1=kb0+4; }
        if (tid==0){
          if (kb1>64) wait_cnt(&g_cnt[(C_BA+rb)*32],8);
          for (int hg=kb0>>4; hg<4 && hg*16<kb1; hg++) wait_cnt(&g_cnt[(C_XA+rb*4+hg)*32],4);
        }
        float acc[144];
        gemm_main(acc,sb,itc,&tm.ao,&tm.wo,&tm.wob,64,kb0,kb1,rb*128,nt*288);
        bool fin=true;
        if (!whole){
          float4* slab0 = (float4*)g_part + (size_t)(rb<15 ? tile*5 : 150+nt*17)*(PSL/4) + tid;
          float4* my = slab0 + (size_t)sp*(PSL/4);
          #pragma unroll
          for (int q=0;q<36;q++) __stcg(my+q*256, make_float4(acc[4*q],acc[4*q+1],acc[4*q+2],acc[4*q+3]));
          __threadfence();
          __syncthreads();
          if (tid==0){ unsigned old=atomicAdd(&g_cnt[(C_DONE+tile)*32],1); __threadfence(); sh[1]=old; }
          __syncthreads();
          fin = (sh[1]==(unsigned)(nsp-1));
          if (fin){
            for (int o=0;o<nsp;o++){ if (o==sp) continue;
              const float4* src=slab0+(size_t)o*(PSL/4);
              #pragma unroll
              for (int q0=0;q0<36;q0+=12){
                float4 p[12];
                #pragma unroll
                for (int q=0;q<12;q++) p[q]=ld_relaxed_v4(src+(q0+q)*256);
                #pragma unroll
                for (int q=0;q<12;q++){ acc[4*(q0+q)]+=p[q].x; acc[4*(q0+q)+1]+=p[q].y; acc[4*(q0+q)+2]+=p[q].z; acc[4*(q0+q)+3]+=p[q].w; }
              }
            }
          }
        }
        if (fin){
          bf16* dst = out + (size_t)(rb*128+16*w+g)*DM + nt*288 + 2*t;
          #pragma unroll
          for (int jn=0;jn<36;jn++){ *(uint32_t*)(dst+8*jn)=pack2(acc[4*jn],acc[4*jn+1]); *(uint32_t*)(dst+8*DM+8*jn)=pack2(acc[4*jn+2],acc[4*jn+3]); }
        }
      }
    }
  }
}
typedef CUresult (*EncFn)(CUtensorMap*, CUtensorMapDataType, cuuint32_t, void*, const cuuint64_t*, const cuuint64_t*, const cuuint32_t*, const cuuint32_t*, CUtensorMapInterleave, CUtensorMapSwizzle, CUtensorMapL2promotion, CUtensorMapFloatOOBfill);
static void enc2d(EncFn fn, CUtensorMap* tm, const void* p, uint64_t cols, uint64_t rows, uint32_t bc, uint32_t br){
  cuuint64_t gd[2]={cols,rows}; cuuint64_t gs[1]={cols*2}; cuuint32_t bd[2]={bc,br}; cuuint32_t es[2]={1,1};
  fn(tm,CU_TENSOR_MAP_DATA_TYPE_BFLOAT16,2,(void*)p,gd,gs,bd,es,CU_TENSOR_MAP_INTERLEAVE_NONE,CU_TENSOR_MAP_SWIZZLE_128B,CU_TENSOR_MAP_L2_PROMOTION_L2_128B,CU_TENSOR_MAP_FLOAT_OOB_FILL_NONE);
}
extern "C" void kernel_launch(void* const* d_in, const int* in_sizes, int n_in, void* d_out, int out_size){
  const bf16* x=(const bf16*)d_in[0]; const bf16* mem0=(const bf16*)d_in[1];
  const bf16* Wq=(const bf16*)d_in[2]; const bf16* Wk=(const bf16*)d_in[3]; const bf16* Wv=(const bf16*)d_in[4]; const bf16* Wo=(const bf16*)d_in[5];
  const bf16* wqkv=(const bf16*)d_in[8]; const bf16* wob=(const bf16*)d_in[9]; const bf16* gw=(const bf16*)d_in[10];
  void* fnp=nullptr; cudaDriverEntryPointQueryResult qr;
  cudaGetDriverEntryPoint("cuTensorMapEncodeTiled",&fnp,cudaEnableDefault,&qr);
  EncFn fn=(EncFn)fnp;
  void* ao=nullptr; cudaGetSymbolAddress(&ao,g_ao);
  CUtensorMap tmx; AuxMaps am;
  enc2d(fn,&tmx,x,DM,SEQ,64,32);
  enc2d(fn,&am.x128,x,DM,SEQ,64,128);
  enc2d(fn,&am.ao,ao,AOW,SEQ,64,128);
  enc2d(fn,&am.wo,Wo,DM,4096,64,64);
  enc2d(fn,&am.wob,wob,DM,DM,64,64);
  enc2d(fn,&am.wqkv,wqkv,1728,DM,64,64);
  cudaFuncSetAttribute(chain_kernel, cudaFuncAttributeMaxDynamicSharedMemorySize, CHAIN_SMEM);
  cudaFuncSetAttribute(aux_kernel, cudaFuncAttributeMaxDynamicSharedMemorySize, AUX_SMEM);
  chain_kernel<<<96,384,CHAIN_SMEM,cudaStreamPerThread>>>(tmx,x,mem0,Wq,Wk,Wv,Wo);
  cudaLaunchConfig_t cfg={}; cfg.gridDim=dim3(132); cfg.blockDim=dim3(256); cfg.dynamicSmemBytes=AUX_SMEM; cfg.stream=cudaStreamPerThread;
  cudaLaunchAttribute at[1]; at[0].id=cudaLaunchAttributeProgrammaticStreamSerialization; at[0].val.programmaticStreamSerializationAllowed=USE_PDL;
  cfg.attrs=at; cfg.numAttrs=1;
  cudaLaunchKernelEx(&cfg, aux_kernel, am, x, gw, (bf16*)d_out);
}
```

```cpp
#include <cuda_runtime.h>
#include <cuda_bf16.h>
#include <cuda.h>
#include <stdint.h>

typedef __nv_bfloat16 bf16;
#define SPR 2
#define ROT 1
#define EB7 1
#define ROTJ j
#define ZAT 1
#define PK 232
#define PS 32
#define LDK 8
#define RV 2
#define QREG 184
#define AREG 136
#define STR_(x) #x
#define STR(x) STR_(x)
#define WJQ 1
#define WJ 2
#define WOC 1
#define XA 0
#define DOX 1
#define USE_PDL 1
constexpr unsigned SEGFLAG_N=96;
constexpr int SEQ=2048, DM=576, NH=32, NSEG=64;

constexpr int NRING=8;
__device__ uint4 g_acc[NRING*768*SPR];
__device__ uint4 g_qx[NSEG*NH*512];
__device__ uint4 g_kx[NSEG*NH*512];
__device__ uint4 g_vx[NSEG*NH*512];
__device__ uint2 g_km[NSEG*NH*256];
__device__ uint2 g_vm[NSEG*NH*256];
__device__ unsigned g_epoch;
__device__ uint4 g_slot[96];
__device__ unsigned g_rep[4*128];
__device__ unsigned g_segflag[NSEG*32];
__device__ __forceinline__ unsigned gtime(){ unsigned v; asm volatile("mov.u32 %0, %%globaltimer_lo;":"=r"(v)::"memory"); return v; }
__device__ __forceinline__ unsigned gtime_v(unsigned z){ unsigned v=0; asm volatile("{.reg .pred p; setp.eq.u32 p,%1,0; @p mov.u32 %0, %%globaltimer_lo;}":"+r"(v):"r"(z):"memory"); return v; }


__device__ __forceinline__ uint32_t smem_u32(const void* p){ return (uint32_t)__cvta_generic_to_shared(p); }
__device__ __forceinline__ uint32_t mapa(uint32_t a, int r){ uint32_t o; asm("mapa.shared::cluster.u32 %0,%1,%2;":"=r"(o):"r"(a),"r"(r)); return o; }
__device__ __forceinline__ uint32_t movm(uint32_t a){ uint32_t d; asm volatile("movmatrix.sync.aligned.m8n8.trans.b16 %0,%1;":"=r"(d):"r"(a)); return d; }
__device__ __forceinline__ uint32_t pack2(float lo, float hi){ uint32_t d; asm("cvt.rn.bf16x2.f32 %0,%1,%2;":"=r"(d):"f"(hi),"f"(lo)); return d; }
__device__ __forceinline__ void mma16816(float* d, uint32_t a0,uint32_t a1,uint32_t a2,uint32_t a3, uint32_t b0, uint32_t b1){
  asm volatile("mma.sync.aligned.m16n8k16.row.col.f32.bf16.bf16.f32 {%0,%1,%2,%3},{%4,%5,%6,%7},{%8,%9},{%0,%1,%2,%3};"
   : "+f"(d[0]),"+f"(d[1]),"+f"(d[2]),"+f"(d[3]) : "r"(a0),"r"(a1),"r"(a2),"r"(a3),"r"(b0),"r"(b1));
}
__device__ __forceinline__ void mma1688(float* d, uint32_t a0,uint32_t a1, uint32_t b0){
  asm volatile("mma.sync.aligned.m16n8k8.row.col.f32.bf16.bf16.f32 {%0,%1,%2,%3},{%4,%5},{%6},{%0,%1,%2,%3};"
   : "+f"(d[0]),"+f"(d[1]),"+f"(d[2]),"+f"(d[3]) : "r"(a0),"r"(a1),"r"(b0));
}
__device__ __forceinline__ void ldsm4(uint32_t& r0,uint32_t& r1,uint32_t& r2,uint32_t& r3,uint32_t addr){
  asm volatile("ldmatrix.sync.aligned.m8n8.x4.shared.b16 {%0,%1,%2,%3},[%4];":"=r"(r0),"=r"(r1),"=r"(r2),"=r"(r3):"r"(addr):"memory");
}
__device__ __forceinline__ void ldsm4t(uint32_t& r0,uint32_t& r1,uint32_t& r2,uint32_t& r3,uint32_t addr){
  asm volatile("ldmatrix.sync.aligned.m8n8.x4.trans.shared.b16 {%0,%1,%2,%3},[%4];":"=r"(r0),"=r"(r1),"=r"(r2),"=r"(r3):"r"(addr):"memory");
}
__device__ __forceinline__ void ldsm2(uint32_t& r0,uint32_t& r1,uint32_t addr){
  asm volatile("ldmatrix.sync.aligned.m8n8.x2.shared.b16 {%0,%1},[%2];":"=r"(r0),"=r"(r1):"r"(addr):"memory");
}
__device__ __forceinline__ void mbar_init(uint32_t a, int cnt){ asm volatile("mbarrier.init.shared.b64 [%0], %1;"::"r"(a),"r"(cnt):"memory"); }
__device__ __forceinline__ void mbar_expect(uint32_t a, uint32_t tx){ asm volatile("mbarrier.arrive.expect_tx.shared.b64 _, [%0], %1;"::"r"(a),"r"(tx):"memory"); }
__device__ __forceinline__ void mbar_arrive(uint32_t a){ asm volatile("mbarrier.arrive.shared.b64 _, [%0];"::"r"(a):"memory"); }
__device__ __forceinline__ void mbar_wait(uint32_t a, uint32_t par){
  uint32_t done=0; int it=0;
  do { asm volatile("{.reg .pred p; mbarrier.try_wait.parity.shared.b64 p,[%1],%2; selp.u32 %0,1,0,p;}":"=r"(done):"r"(a),"r"(par):"memory"); } while(!done && ++it<(1<<22));
}
__device__ __forceinline__ void bar_sync(int id, int n){ asm volatile("bar.sync %0,%1;"::"r"(id),"r"(n):"memory"); }
__device__ __forceinline__ void bar_arrive(int id, int n){ asm volatile("bar.arrive %0,%1;"::"r"(id),"r"(n):"memory"); }
__device__ __forceinline__ float4 ld_relaxed_v4(const float4* p){
  float4 v; asm volatile("ld.relaxed.gpu.global.v4.f32 {%0,%1,%2,%3}, [%4];" : "=f"(v.x),"=f"(v.y),"=f"(v.z),"=f"(v.w) : "l"(p) : "memory"); return v;
}
__device__ __forceinline__ uint4 ld_cg_v4(const uint4* p){
  uint4 v; asm volatile("ld.relaxed.gpu.global.v4.u32 {%0,%1,%2,%3}, [%4];" : "=r"(v.x),"=r"(v.y),"=r"(v.z),"=r"(v.w) : "l"(p) : "memory"); return v;
}
__device__ __forceinline__ void red_v4(float4* p, float a, float b, float c, float d){
  asm volatile("red.relaxed.gpu.global.add.v4.f32 [%0], {%1,%2,%3,%4};" :: "l"(p), "f"(a),"f"(b),"f"(c),"f"(d) : "memory");
}
__device__ __forceinline__ void red_h4(uint4* p, uint32_t a, uint32_t b, uint32_t c, uint32_t d){
  asm volatile("red.relaxed.gpu.global.add.noftz.v4.f16x2 [%0], {%1,%2,%3,%4};" :: "l"(p), "r"(a),"r"(b),"r"(c),"r"(d) : "memory");
}
__device__ __forceinline__ uint32_t packh(float lo, float hi){ uint32_t d; asm("cvt.rn.f16x2.f32 %0,%1,%2;":"=r"(d):"f"(hi),"f"(lo)); return d; }
__device__ __forceinline__ uint32_t h2bf(uint32_t h){ float lo,hi; asm("{.reg .f16 a,b; mov.b32 {a,b},%2; cvt.f32.f16 %0,a; cvt.f32.f16 %1,b;}":"=f"(lo),"=f"(hi):"r"(h)); return pack2(lo,hi); }
__device__ __forceinline__ void tma_load_2d(uint32_t dst, const CUtensorMap* tm, int c0, int c1, uint32_t mbar){
  asm volatile("cp.async.bulk.tensor.2d.shared::cluster.global.mbarrier::complete_tx::bytes [%0], [%1, {%3, %4}], [%2];"
    :: "r"(dst), "l"((uint64_t)tm), "r"(mbar), "r"(c0), "r"(c1) : "memory");
}
__device__ __forceinline__ void wgmma_rs_n32(float* d, uint32_t a0,uint32_t a1,uint32_t a2,uint32_t a3, uint64_t desc, int scale_d){
  asm volatile("{.reg .pred p; setp.ne.b32 p, %21, 0;\n"
   "wgmma.mma_async.sync.aligned.m64n32k16.f32.bf16.bf16 {%0,%1,%2,%3,%4,%5,%6,%7,%8,%9,%10,%11,%12,%13,%14,%15}, {%16,%17,%18,%19}, %20, p, 1, 1, 0;}"
   : "+f"(d[0]),"+f"(d[1]),"+f"(d[2]),"+f"(d[3]),"+f"(d[4]),"+f"(d[5]),"+f"(d[6]),"+f"(d[7]),"+f"(d[8]),"+f"(d[9]),"+f"(d[10]),"+f"(d[11]),"+f"(d[12]),"+f"(d[13]),"+f"(d[14]),"+f"(d[15])
   : "r"(a0),"r"(a1),"r"(a2),"r"(a3),"l"(desc),"r"(scale_d));
}
__device__ __forceinline__ void wgmma_ss_n32(float* d, uint64_t da, uint64_t desc){
  asm volatile("wgmma.mma_async.sync.aligned.m64n32k16.f32.bf16.bf16 {%0,%1,%2,%3,%4,%5,%6,%7,%8,%9,%10,%11,%12,%13,%14,%15}, %16, %17, 1, 1, 1, 0, 0;"
   : "+f"(d[0]),"+f"(d[1]),"+f"(d[2]),"+f"(d[3]),"+f"(d[4]),"+f"(d[5]),"+f"(d[6]),"+f"(d[7]),"+f"(d[8]),"+f"(d[9]),"+f"(d[10]),"+f"(d[11]),"+f"(d[12]),"+f"(d[13]),"+f"(d[14]),"+f"(d[15])
   : "l"(da),"l"(desc));
}
__device__ __forceinline__ unsigned absmax8(uint4 v){ unsigned m=__vmaxu2(__vmaxu2(v.x&0x7fff7fffu,v.y&0x7fff7fffu),__vmaxu2(v.z&0x7fff7fffu,v.w&0x7fff7fffu)); return m; }
__device__ __forceinline__ unsigned ld_flag(const unsigned* p){ unsigned v; asm volatile("ld.relaxed.gpu.global.u32 %0,[%1];":"=r"(v):"l"(p):"memory"); return v; }

constexpr int XBUF = 36864;
constexpr int NXB = 3;
constexpr int SM_X = 0;
constexpr int SM_KV = SM_X + NXB*XBUF;
constexpr int SM_AS = SM_KV + 32768;
constexpr int SM_WJ = SM_AS + 4096;
constexpr int SM_XR = SM_WJ + 4*WJ*3*512;
constexpr int SM_MEM = SM_XR + 8192;
constexpr int SM_Q = SM_MEM + 8*1168;
constexpr int SM_S = SM_Q + 3*2048;
constexpr int SM_O = SM_S + 8*128*4 + 64;
constexpr int SM_BAR = SM_O + 8*272;
constexpr int SM_CT = SM_BAR + 64;
constexpr int SM_TS = SM_CT + 192;
constexpr int CHAIN_SMEM = SM_TS;
__device__ __forceinline__ float ex2(float x){ float y; asm("ex2.approx.ftz.f32 %0,%1;":"=f"(y):"f"(x)); return y; }
__device__ __forceinline__ float rcpa(float x){ float y; asm("rcp.approx.ftz.f32 %0,%1;":"=f"(y):"f"(x)); return y; }
__device__ __forceinline__ uint4 lds128(uint32_t a){ uint4 v; asm volatile("ld.shared.v4.u32 {%0,%1,%2,%3},[%4];":"=r"(v.x),"=r"(v.y),"=r"(v.z),"=r"(v.w):"r"(a):"memory"); return v; }
__device__ __forceinline__ uint2 lds64(uint32_t a){ uint2 v; asm volatile("ld.shared.v2.u32 {%0,%1},[%2];":"=r"(v.x),"=r"(v.y):"r"(a):"memory"); return v; }
__device__ __forceinline__ void sts32(uint32_t a, uint32_t v){ asm volatile("st.shared.u32 [%0],%1;"::"r"(a),"r"(v):"memory"); }
__device__ __forceinline__ void stsf(uint32_t a, float v){ asm volatile("st.shared.f32 [%0],%1;"::"r"(a),"f"(v):"memory"); }
__device__ __forceinline__ void bulk_g2s(uint32_t dst, const void* src, uint32_t bytes, uint32_t mbar){
  asm volatile("cp.async.bulk.shared::cluster.global.mbarrier::complete_tx::bytes [%0],[%1],%2,[%3];"::"r"(dst),"l"(src),"r"(bytes),"r"(mbar):"memory");
}


__device__ __forceinline__ void bulk_s2g(void* dst, uint32_t src, uint32_t bytes){ asm volatile("cp.async.bulk.global.shared::cta.bulk_group [%0],[%1],%2;"::"l"(dst),"r"(src),"r"(bytes):"memory"); }
__device__ __forceinline__ uint32_t ldg32p(const void* p){ uint32_t v; asm volatile("ld.global.nc.L2::128B.u32 %0,[%1];":"=r"(v):"l"(p)); return v; }
__device__ __forceinline__ uint2 ldg64p(const void* p){ uint2 v; asm volatile("ld.global.nc.L2::256B.v2.u32 {%0,%1},[%2];":"=r"(v.x),"=r"(v.y):"l"(p)); return v; }
__device__ __forceinline__ void sts128f(uint32_t a, float x, float y, float z, float w){ asm volatile("st.shared.v4.f32 [%0],{%1,%2,%3,%4};"::"r"(a),"f"(x),"f"(y),"f"(z),"f"(w):"memory"); }
__device__ __forceinline__ uint32_t lds32(uint32_t a){ uint32_t v; asm volatile("ld.shared.u32 %0,[%1];":"=r"(v):"r"(a):"memory"); return v; }
__device__ __forceinline__ void tma_load_3d(uint32_t dst, const CUtensorMap* tm, int c0, int c1, int c2, uint32_t mbar){
  asm volatile("cp.async.bulk.tensor.3d.shared::cluster.global.mbarrier::complete_tx::bytes [%0], [%1, {%3, %4, %5}], [%2];"
    :: "r"(dst), "l"((uint64_t)tm), "r"(mbar), "r"(c0), "r"(c1), "r"(c2) : "memory");
}
__device__ __forceinline__ void tma_load_2d_mc(uint32_t dst, const CUtensorMap* tm, int c0, int c1, uint32_t mbar, uint16_t mask){
  asm volatile("cp.async.bulk.tensor.2d.shared::cluster.global.mbarrier::complete_tx::bytes.multicast::cluster [%0], [%1, {%3, %4}], [%2], %5;"
    :: "r"(dst), "l"((uint64_t)tm), "r"(mbar), "r"(c0), "r"(c1), "h"(mask) : "memory");
}
__device__ __forceinline__ float bf_lo(uint32_t v){ return __uint_as_float(v<<16); }
__device__ __forceinline__ float bf_hi(uint32_t v){ return __uint_as_float(v&0xffff0000u); }
#define F(x) __uint_as_float(x)

constexpr int AOW = 4672;
__device__ bf16 g_ao[SEQ*AOW];
__device__ bf16 g_bq[96*SEQ*24];
__device__ float g_gate[SEQ];
constexpr int PSL = 128*288;
__device__ float4 g_part[32*PSL/4];
constexpr int NCNT=100+48*8;
__device__ unsigned g_cnt[NCNT*32];
constexpr int C_QH=0, C_BQ=1, C_RDY=17  , C_XS=33  , C_DONE=65  , C_GATE=97, C_EXIT=98, C_DONS=100  ;
constexpr int A_STAGE = 16384+5*8192;
constexpr int A_NST = 4;
constexpr int A_BAR = A_NST*A_STAGE;
constexpr int AUX_SMEM = A_BAR + 256;
constexpr int NTASK=338;
__constant__ unsigned c_task[NTASK]={0x2u,0x802u,0x1002u,0x1802u,0x2002u,0x2802u,0xau,0x80au,0x100au,0x180au,0x200au,0x280au,0x12u,0x812u,0x1012u,0x1812u,0x2012u,0x2812u,0x1au,0x81au,0x101au,0x181au,0x201au,0x281au,0x22u,0x822u,0x1022u,0x1822u,0x2022u,0x2822u,0x2au,0x82au,0x102au,0x182au,0x100004u,0x100804u,0x10000cu,0x10080cu,0x100014u,0x100814u,0x3u,0x803u,0x1003u,0x1803u,0xbu,0x80bu,0x100bu,0x180bu,0x13u,0x10001cu,0x10081cu,0x813u,0x1013u,0x1813u,0x1bu,0x81bu,0x101bu,0x181bu,0x23u,0x100024u,0x100824u,0x10002cu,0x10082cu,0x100034u,0x100834u,0x10003cu,0x10083cu,0x823u,0x100044u,0x100844u,0x10004cu,0x10084cu,0x1023u,0x1823u,0x2bu,0x82bu,0x102bu,0x182bu,0x202au,0x282au,0x33u,0x833u,0x1033u,0x1833u,0xa480005u,0xa48000du,0x100054u,0x100854u,0x10005cu,0x10085cu,0x100064u,0x100864u,0x10006cu,0x10086cu,0x100074u,0x100874u,0x3bu,0x83bu,0x103bu,0x183bu,0x32u,0x832u,0x1032u,0x1832u,0x10007cu,0x10087cu,0x100084u,0x100884u,0x2032u,0x2832u,0x43u,0x10008cu,0x10088cu,0x843u,0x1043u,0x1843u,0x4bu,0x100094u,0x100894u,0xa480015u,0xa48001du,0x84bu,0x104bu,0x10009cu,0x10089cu,0x1000a4u,0x1008a4u,0x184bu,0x3au,0x1000acu,0x1008acu,0x83au,0x1000b4u,0x1008b4u,0x103au,0x183au,0x203au,0x283au,0x1000bcu,0x1008bcu,0x53u,0x853u,0x1053u,0x1000c4u,0x1008c4u,0x1853u,0x1000ccu,0x1008ccu,0x5bu,0x85bu,0x105bu,0x1000d4u,0x1008d4u,0xa480025u,0xa48002du,0x1000dcu,0x1008dcu,0x1000e4u,0x1008e4u,0x185bu,0x63u,0x863u,0x1000ecu,0x1008ecu,0x1063u,0x1000f4u,0x1008f4u,0x1863u,0x6bu,0x86bu,0x1000fcu,0x1008fcu,0x100104u,0x100904u,0x106bu,0x186bu,0x10010cu,0x10090cu,0x73u,0x100114u,0x100914u,0x873u,0xa480035u,0xa48003du,0x1073u,0x10011cu,0x10091cu,0x1873u,0x7bu,0x100124u,0x100924u,0x10012cu,0x10092cu,0x87bu,0x107bu,0x100134u,0x100934u,0x187bu,0x10013cu,0x10093cu,0x100144u,0x100944u,0x10014cu,0x10094cu,0x100154u,0x100954u,0x11200045u,0x1120004du,0x12492045u,0x1249204du,0x10015cu,0x10095cu,0x100164u,0x100964u,0x4a4a01e6u,0x4a4a01eeu,0x4a4a01f6u,0x10016cu,0x10096cu,0x100174u,0x100974u,0x10017cu,0x10097cu,0x100184u,0x100984u,0x10018cu,0x10098cu,0x100194u,0x100994u,0x18c00055u,0x18c0005du,0x1980c055u,0x1980c05du,0x1a498055u,0x1a49805du,0x10019cu,0x10099cu,0x1001a4u,0x1009a4u,0x1001acu,0x1009acu,0x1001b4u,0x1009b4u,0x20c00186u,0x1001bcu,0x1009bcu,0x1001c4u,0x1009c4u,0x20c0018eu,0x20c00196u,0x1001ccu,0x1009ccu,0x2160c186u,0x2160c18eu,0x1001d4u,0x1009d4u,0x2160c196u,0x21e16186u,0x1001dcu,0x1009dcu,0x801e4u,0x809e4u,0x811e4u,0x819e4u,0x21e1618eu,0x21e16196u,0x2249e186u,0x801ecu,0x809ecu,0x811ecu,0x819ecu,0x801f4u,0x809f4u,0x811f4u,0x819f4u,0x801fcu,0x809fcu,0x811fcu,0x819fcu,0x2249e18eu,0x2249e196u,0x287001a6u,0x287001aeu,0x287001b6u,0x28e871a6u,0x28e871aeu,0x28e871b6u,0x2958e9a6u,0x2958e9aeu,0x2958e9b6u,0x29d159a6u,0x29d159aeu,0x29d159b6u,0x2a49d1a6u,0x2a49d1aeu,0x2a49d1b6u,0x306001c6u,0x306001ceu,0x306001d6u,0x30c061c6u,0x30c061ceu,0x30c061d6u,0x3120c1c6u,0x3120c1ceu,0x3120c1d6u,0x318121c6u,0x318121ceu,0x318121d6u,0x31e181c6u,0x31e181ceu,0x31e181d6u,0x3249e1c6u,0x3249e1ceu,0x3249e1d6u,0x484001e6u,0x484001eeu,0x484001f6u,0x488041e6u,0x488041eeu,0x488041f6u,0x48c081e6u,0x48c081eeu,0x48c081f6u,0x4900c1e6u,0x4900c1eeu,0x4900c1f6u,0x494101e6u,0x494101eeu,0x494101f6u,0x498141e6u,0x498141eeu,0x498141f6u,0x49c181e6u,0x49c181eeu,0x49c181f6u,0x4a01c1e6u,0x4a01c1eeu,0x4a01c1f6u};
#define NOAHEAD 80
#define PACE 16
enum { K_END=0, K_GATE, K_BQ, K_BA, K_XA, K_GM, K_GS, K_GU };

__global__ void __cluster_dims__(3,1,1) __launch_bounds__(384,1)
chain_kernel(const __grid_constant__ CUtensorMap tmx, const bf16* __restrict__ x, const bf16* __restrict__ mem0, const bf16* __restrict__ Wq, const bf16* __restrict__ Wk,
             const bf16* __restrict__ Wv, const bf16* __restrict__ Wo, const bf16* __restrict__ gate_w)
{
  extern __shared__ __align__(1024) unsigned char sm[];
  const uint32_t sb = smem_u32(sm);
  const int tid = threadIdx.x, lane = tid&31, warp = tid>>5, g = lane>>2, t = lane&3;
  const int j = blockIdx.x % 3, h = blockIdx.x / 3;
  const uint32_t bar_qkv = sb+SM_BAR, bar_x = sb+SM_BAR+16, bar_kv = sb+SM_BAR+48;
  const uint32_t ct = sb+SM_CT;
  if (warp < 8){
    asm volatile("setmaxnreg.inc.sync.aligned.u32 " STR(QREG) ";");
    const int w = __shfl_sync(~0u,warp,0);
    uint32_t A[36][4];
    {
      const bf16* W = (j==0?Wq:(j==1?Wk:Wv)) + h*128 + 16*w + 4*t + (size_t)g*4096;
      #pragma unroll
      for (int c=0;c<3;c++){
        const bf16* Wc = W + (size_t)(((c+ROTJ)%3)*192)*4096;
        #pragma unroll
        for (int k=0;k<12;k++){
          uint2 lo = ldg64p(Wc + (size_t)(16*k)*4096);
          uint2 hi = ldg64p(Wc + (size_t)(16*k+8)*4096);
          A[c*12+k][0]=lo.x; A[c*12+k][1]=lo.y; A[c*12+k][2]=hi.x; A[c*12+k][3]=hi.y;
        }
      }
      #pragma unroll
      for (int k=0;k<36;k++){ if (k==LDK && blockIdx.x) asm volatile("griddepcontrol.launch_dependents;":::"memory"); A[k][0]=movm(A[k][0]); A[k][1]=movm(A[k][1]); A[k][2]=movm(A[k][2]); A[k][3]=movm(A[k][3]); }
      asm volatile("stmatrix.sync.aligned.m8n8.x4.shared.b16 [%0],{%1,%2,%3,%4};"::"r"(sb+SM_AS+w*512+((lane>>3)&1)*256+(lane>>4)*128+(lane&7)*16),"r"(A[35][0]),"r"(A[35][1]),"r"(A[35][2]),"r"(A[35][3]):"memory");
      asm volatile("fence.proxy.async.shared::cta;":::"memory");
      unsigned r=0;
      if (j==2){
        float n0[4]={0,0,0,0}, n1[4]={0,0,0,0};
        #pragma unroll
        for (int k=0;k<36;k++) mma16816((k&1)?n1:n0, A[k][0]&0x7fff7fffu,A[k][1]&0x7fff7fffu,A[k][2]&0x7fff7fffu,A[k][3]&0x7fff7fffu, 0x3F803F80u,0x3F803F80u);
        r = __reduce_max_sync(~0u, __float_as_uint(fmaxf(n0[0]+n1[0],n0[2]+n1[2])));
      }
      if (lane==0) sts32(ct+(24+w)*4, r);
      bar_arrive(4,384);
      bar_sync(9,384);
    }
    const uint32_t lda = sb + SM_MEM + (lane&7)*1168 + (lane>>3)*16;
    int xb = 0, xph = 0;
    for (int s=-3;s<NSEG;s++){
      const bool dox = s+3<NSEG && (DOX || s<0);
      float d[16];
      const uint64_t desc = ((uint64_t)(((sb+SM_X+xb*XBUF)&0x3FFFF)>>4)) | ((uint64_t)1<<16) | ((uint64_t)(1024>>4)<<32) | ((uint64_t)1<<62);
      if (s>=0){
        float c[3][4];
        #pragma unroll
        for (int q=0;q<3;q++){ c[q][0]=c[q][1]=c[q][2]=c[q][3]=0.f; }
        #pragma unroll
        for (int ch=0;ch<3;ch++){
          bar_sync(1+ch,384);
          uint32_t b[12][2];
          #pragma unroll
          for (int q=0;q<6;q++) ldsm4(b[2*q][0],b[2*q][1],b[2*q+1][0],b[2*q+1][1], lda + (ch*12+2*q)*32);
          #pragma unroll
          for (int q=0;q<12;q++){ const int k=ch*12+q; mma16816(c[k%3], A[k][0],A[k][1],A[k][2],A[k][3], b[q][0],b[q][1]); }
        }
        const float us = F(lds32(ct+14*4));
        const uint4 ra = lds128(ct+16);
        uint32_t p0 = pack2(((c[0][0]+c[1][0])+c[2][0])*us, ((c[0][1]+c[1][1])+c[2][1])*us);
        uint32_t p1 = pack2(((c[0][2]+c[1][2])+c[2][2])*us, ((c[0][3]+c[1][3])+c[2][3])*us);
        if (j<2){ p0=movm(p0); p1=movm(p1); }
        if (s<NSEG-1){
          asm volatile("st.async.shared::cluster.mbarrier::complete_tx::bytes.v2.b32 [%0], {%1,%2}, [%3];"::"r"(ra.x+tid*8),"r"(p0),"r"(p1),"r"(ra.z):"memory");
          asm volatile("st.async.shared::cluster.mbarrier::complete_tx::bytes.v2.b32 [%0], {%1,%2}, [%3];"::"r"(ra.y+tid*8),"r"(p0),"r"(p1),"r"(ra.w):"memory");
        }
        asm volatile("st.shared.v2.b32 [%0],{%1,%2};"::"r"(sb+SM_Q+j*2048+tid*8),"r"(p0),"r"(p1):"memory");
        __syncwarp();
        if (lane==0 && s<NSEG-1) mbar_arrive(bar_qkv);
        asm volatile("fence.proxy.async.shared::cta;":::"memory");
        bar_sync(8, s<NSEG-1 ? 384 : 256);
      }
      #pragma unroll
      for (int q=0;q<16;q++) d[q]=0.f;
      if (dox) mbar_wait(bar_x+8*xb, xph);
      if (dox && XA>0){
        asm volatile("wgmma.fence.sync.aligned;":::"memory");
        #pragma unroll
        for (int k=0;k<XA;k++) wgmma_rs_n32(d, A[k][0],A[k][1],A[k][2],A[k][3], desc + (uint64_t)((((k/12+ROTJ)%3)*12288 + ((k%12)>>2)*4096 + (k&3)*32)>>4), k>0);
        asm volatile("wgmma.commit_group.sync.aligned;":::"memory");
      }
      if (s>=0){
      if (tid==64 && s+4<NSEG && DOX){ const int pb=(s+4)%NXB; mbar_expect(bar_x+8*pb, XBUF);
        asm volatile("cp.async.bulk.tensor.3d.shared::cluster.global.mbarrier::complete_tx::bytes.multicast::cluster [%0], [%1, {%3, %4, %5}], [%2], %6;"
          :: "r"(sb+SM_X+pb*XBUF+j*12288), "l"((uint64_t)&tmx), "r"(bar_x+8*pb), "r"(0), "r"((s+4)*32), "r"(3*j), "h"((uint16_t)7) : "memory"); }
        if (ZAT){ if (w==3 && s>=4) asm volatile("red.relaxed.gpu.global.and.b64 [%0],0;"::"l"((char*)(g_acc+((s+4)&(NRING-1))*768*SPR + blockIdx.x*8*SPR) + lane*8):"memory"); }
        else if (w==3 && lane<8*SPR && s>=4) g_acc[((s+4)&(NRING-1))*768*SPR + blockIdx.x*8*SPR + lane] = make_uint4(0,0,0,0);
        if (tid==0){
          if (s>0){ asm volatile("cp.async.bulk.wait_group 0;":::"memory"); asm volatile("red.relaxed.gpu.global.add.u32 [%0],1;"::"l"(g_segflag+(s-1)*32):"memory"); }
      if (s+1<NSEG-1){ const uint32_t bb=((s+1)&1); mbar_expect(bar_kv+8*bb,16384);
        if (j>0) asm volatile("cp.async.bulk.shared::cluster.global.mbarrier::complete_tx::bytes.multicast::cluster [%0],[%1],%2,[%3],%4;"::"r"(sb+SM_KV+bb*16384+(j-1)*8192),"l"((j==1?g_kx:g_vx)+(size_t)((s+1)*NH+h)*512),"r"(8192),"r"(bar_kv+8*bb),"h"((uint16_t)7):"memory"); }
          if (j>=1) bulk_s2g((j==1?g_km:g_vm) + (size_t)(s*NH+h)*256, sb+SM_Q+j*2048, 2048);
          if (s>0 && s+2<NSEG && DOX) bulk_s2g((j==0?g_qx:(j==1?g_kx:g_vx)) + (size_t)((s+2)*NH+h)*512, sb+SM_XR, 8192);
          asm volatile("cp.async.bulk.commit_group;":::"memory");
          if (s<NSEG-1) asm volatile("cp.async.bulk.wait_group.read 0;":::"memory");
          else { asm volatile("cp.async.bulk.wait_group 0;":::"memory"); asm volatile("red.relaxed.gpu.global.add.u32 [%0],1;"::"l"(g_segflag+s*32):"memory"); }
        }
        __syncwarp();
        if (s<NSEG-1) bar_sync(7,384);
      }
      if (dox){
        asm volatile("wgmma.fence.sync.aligned;":::"memory");
        #pragma unroll
        for (int k=XA;k<35;k++) wgmma_rs_n32(d, A[k][0],A[k][1],A[k][2],A[k][3], desc + (uint64_t)((((k/12+ROTJ)%3)*12288 + ((k%12)>>2)*4096 + (k&3)*32)>>4), k>0);
        wgmma_ss_n32(d, ((uint64_t)(((sb+SM_AS+(w>>2)*2048)&0x3FFFF)>>4)) | ((uint64_t)(128>>4)<<16) | ((uint64_t)(256>>4)<<32), desc + (uint64_t)((((2+ROTJ)%3)*12288+2*4096+3*32)>>4));
        asm volatile("wgmma.commit_group.sync.aligned;":::"memory");
        asm volatile("wgmma.wait_group.sync.aligned 0;":::"memory");
        uint32_t p[8];
        #pragma unroll
        for (int n=0;n<4;n++){ p[2*n]=pack2(d[4*n],d[4*n+1]); p[2*n+1]=pack2(d[4*n+2],d[4*n+3]); }
        if (s<0){
          uint4* gx = (j==0?g_qx:(j==1?g_kx:g_vx)) + (size_t)((s+3)*NH+h)*512;
          if (j<2){
            #pragma unroll
            for (int n=0;n<8;n++) ((uint32_t*)gx)[(n>>2)*1024 + w*128 + (n&3)*32 + lane] = p[n];
          } else { gx[w*64+lane]=make_uint4(p[0],p[1],p[2],p[3]); gx[w*64+32+lane]=make_uint4(p[4],p[5],p[6],p[7]); }
          if (s==-3){ bar_sync(8,256); if (tid==0){ mbar_expect(bar_x, XBUF); for (int q=0;q<3;q++) tma_load_3d(sb+SM_X+q*12288,&tmx,0,3*32,3*q,bar_x); } }
        } else {
          if (j<2){
            const uint32_t st = sb+SM_XR+tid*16;
            asm volatile("stmatrix.sync.aligned.m8n8.x4.shared.b16 [%0],{%1,%2,%3,%4};"::"r"(st),"r"(p[0]),"r"(p[1]),"r"(p[2]),"r"(p[3]):"memory");
            asm volatile("stmatrix.sync.aligned.m8n8.x4.shared.b16 [%0],{%1,%2,%3,%4};"::"r"(st+4096),"r"(p[4]),"r"(p[5]),"r"(p[6]),"r"(p[7]):"memory");
          } else {
            const uint32_t st = sb+SM_XR+lane*16+w*1024;
            sts128f(st, F(p[0]),F(p[1]),F(p[2]),F(p[3])); sts128f(st+512, F(p[4]),F(p[5]),F(p[6]),F(p[7]));
          }
        }
        if (++xb==NXB){ xb=0; xph^=1; }
      }
      if (s==-1){ __threadfence(); asm volatile("barrier.cluster.arrive.release.aligned;\nbarrier.cluster.wait.acquire.aligned;":::"memory"); }
    }
  } else {
    asm volatile("setmaxnreg.dec.sync.aligned.u32 " STR(AREG) ";");
    const int a = __shfl_sync(~0u,warp,0)-8;
    uint32_t Wf[3][8][4];
    {
      const unsigned tag = *(volatile unsigned*)&g_epoch + 1;
      if (tid==256){
        mbar_init(bar_qkv, 9);
        for (int i=0;i<NXB;i++) mbar_init(bar_x+8*i, 1);
        mbar_init(bar_kv,1); mbar_init(bar_kv+8,1); mbar_init(bar_qkv+8,1);
        asm volatile("fence.mbarrier_init.release.cluster;":::"memory");
        for (int b=0;b<3;b++){ mbar_expect(bar_x+8*b, XBUF); for (int q=0;q<3;q++) tma_load_3d(sb+SM_X+b*XBUF+q*12288,&tmx,0,b*32,3*q,bar_x+8*b); }
        { const int r0=min((int)blockIdx.x*22,SEQ-22); mbar_expect(bar_qkv+8, 22*1152+9216+1152); bulk_g2s(sb+SM_KV, x+(size_t)r0*DM, 22*1152, bar_qkv+8); bulk_g2s(sb+SM_XR, mem0, 8192, bar_qkv+8); bulk_g2s(sb+SM_KV+26624, mem0+4096, 1024, bar_qkv+8); bulk_g2s(sb+SM_KV+25344, gate_w, 1152, bar_qkv+8); }
        sts32(ct+14*4, 0x3f800000u);
        sts32(ct+16, mapa(sb+SM_Q+j*2048,(j+1)%3)); sts32(ct+20, mapa(sb+SM_Q+j*2048,(j+2)%3)); sts32(ct+24, mapa(bar_qkv,(j+1)%3)); sts32(ct+28, mapa(bar_qkv,(j+2)%3));
        sts32(ct+36, 0x7fff7fffu); sts32(ct+40, 0x5000u); sts32(ct+48, 0); sts32(ct+52, 0); sts32(ct+8, 1200); sts32(ct+12, 1200);
      }
      __syncwarp();
      bar_arrive(9,384);
      if (a==3){
        #pragma unroll
        for (int i=0;i<2*SPR;i++) g_acc[blockIdx.x*64*SPR+i*32+lane] = make_uint4(0,0,0,0);
        if (blockIdx.x<4) ((uint4*)g_rep)[blockIdx.x*32+lane]=make_uint4(0,0,0,0);
        if (blockIdx.x==0){ g_segflag[lane*32]=0; g_segflag[(32+lane)*32]=0; for (int i=lane;i<NCNT;i+=32) g_cnt[i*32]=0; }
        __threadfence();
        if (blockIdx.x==0) asm volatile("griddepcontrol.launch_dependents;":::"memory");
      }
      __syncwarp();
      const bf16* W = Wo + (size_t)h*128*DM + 192*j + 48*a + 2*t + (size_t)(4*(g>>1) + (g&1))*DM;
      #pragma unroll
      for (int X=0;X<3;X++)
      #pragma unroll
      for (int k=0;k<8;k++){
        Wf[X][k][0]=ldg32p(W + (size_t)(16*k)*DM + 16*X); Wf[X][k][1]=ldg32p(W + (size_t)(16*k)*DM + 16*X + 8);
        Wf[X][k][2]=ldg32p(W + (size_t)(16*k+2)*DM + 16*X); Wf[X][k][3]=ldg32p(W + (size_t)(16*k+2)*DM + 16*X + 8);
      }
      float mxn=0.f;
      #pragma unroll
      for (int X=0;X<3;X++){
        float n0[4]={0,0,0,0};
        #pragma unroll
        for (int k=0;k<8;k++){
          const uint32_t r0=movm(Wf[X][k][0]), r1=movm(Wf[X][k][1]), r2=movm(Wf[X][k][2]), r3=movm(Wf[X][k][3]);
          Wf[X][k][0]=r0; Wf[X][k][1]=r1; Wf[X][k][2]=r2; Wf[X][k][3]=r3;
          if (k>=8-WJ) *(uint4*)(sm+SM_WJ+((a*WJ+k-(8-WJ))*3+X)*512+lane*16)=make_uint4(r0,r1,r2,r3);
          mma16816(n0, r0&0x7fff7fffu,r1&0x7fff7fffu,r2&0x7fff7fffu,r3&0x7fff7fffu, 0x3F803F80u,0x3F803F80u);
        }
        mxn = fmaxf(mxn,fmaxf(n0[0],n0[2]));
      }
      const unsigned wo1 = __reduce_max_sync(~0u, __float_as_uint(mxn));
      unsigned xm=0, mm=0;
      bar_sync(5,128);
      mbar_wait(bar_qkv+8,0);
      {
        #pragma unroll 1
        for (int i=0;i<5;i++){ const int idx=min(i*128+tid-256,575); uint4 u=lds128(idx<512 ? sb+SM_XR+idx*16 : sb+SM_KV+26624+(idx-512)*16); *(uint4*)(sm+SM_MEM+(idx/72)*1168+(((idx%72)+72-24*(ROTJ))%72)*16)=u; mm=__vmaxu2(mm,absmax8(u)); }
        #define DOT(a,b) (bf_lo(a.x)*bf_lo(b.x)+bf_hi(a.x)*bf_hi(b.x)+bf_lo(a.y)*bf_lo(b.y)+bf_hi(a.y)*bf_hi(b.y)+bf_lo(a.z)*bf_lo(b.z)+bf_hi(a.z)*bf_hi(b.z)+bf_lo(a.w)*bf_lo(b.w)+bf_hi(a.w)*bf_hi(b.w))
        const int row=min((tid-256)>>2,21); float sg=0.f;
        #pragma unroll 2
        for (int c=0;c<18;c++){ uint4 xv=lds128(sb+SM_KV+row*1152+(c*4+t)*16), wv=lds128(sb+SM_KV+25344+(c*4+t)*16); sg+=DOT(xv,wv); xm=__vmaxu2(xm,absmax8(xv)); }
        sg+=__shfl_xor_sync(~0u,sg,1); sg+=__shfl_xor_sync(~0u,sg,2);
        if (t==0) g_gate[min((int)blockIdx.x*22,SEQ-22)+row]=1.f/(1.f+__expf(-sg));
      }
      xm = __reduce_max_sync(~0u,max(xm<<16,xm&0xffff0000u)); mm = __reduce_max_sync(~0u,max(mm<<16,mm&0xffff0000u));
      if (lane==0){ sts32(ct+(20+a)*4, mm); sts32(ct+(32+a)*4, xm); sts32(ct+(36+a)*4, wo1); }
      bar_sync(4,384);
      if (a==1) __threadfence();
      if (a==0){
        if (lane==0){
          uint4 p=lds128(ct+128), q=lds128(ct+144), r=lds128(ct+96), u=lds128(ct+112);
          asm volatile("st.relaxed.gpu.global.v4.u32 [%0],{%1,%2,%3,%4};"::"l"(g_slot+blockIdx.x),"r"(max(max(p.x,p.y),max(p.z,p.w))),"r"(max(max(q.x,q.y),max(q.z,q.w))),
             "r"(max(max(max(r.x,r.y),max(r.z,r.w)),max(max(u.x,u.y),max(u.z,u.w)))),"r"(tag):"memory");
        }
        if (lane==0) sts32(ct+44,tag);
      }
    }
    asm volatile("barrier.cluster.arrive.release.aligned;\nbarrier.cluster.wait.acquire.aligned;":::"memory");
    const float cexp = 0.08838834764831845f*1.4426950408889634f;
    const int ti=a&1, kh=a>>1;
    const uint32_t sts_mem = sb + SM_MEM + (lane&7)*1168 + 96*a + (lane>>3)*16;
    const uint32_t sw0 = sb+SM_S+((2*t)*128+16*(t&1) + 4*(g>>1)+(g&1))*4;
    const int swd = 512 + ((t&1)?-64:64);
    const uint32_t srd = sb+SM_S+(g*128+16*((g^(g>>1))&1)+4*t)*4;
    const uint32_t l8 = sb + lane*8;
    const uint32_t ost = sb+SM_O+(lane&7)*272+(lane>>3)*16;
    const uint32_t zr = lds32(ct+48+(lane&1)*4);
    uint4* ap = g_acc + a*64*SPR + (lane/(8/SPR))*8 + lane%(8/SPR);
    if (tid==256){ const uint4* gk = g_kx + (size_t)h*512; asm volatile("fence.proxy.async;":::"memory"); mbar_expect(bar_kv,16384); bulk_g2s(sb+SM_KV,gk,8192,bar_kv); bulk_g2s(sb+SM_KV+8192,gk+(g_vx-g_kx),8192,bar_kv); }
    constexpr unsigned pK = PK, pS = PS;
    float scl = 1.f;
    unsigned G = 0, tlat = 0;
    for (int s=0;s<NSEG;s++){
      if (s>0){
        uint4 v[6];
        const uint4* ldp = ap + ((s-1)&(NRING-1))*768*SPR;
        const uint4* lp0 = ldp + ((0+ROTJ)%3)*256*SPR + zr; const uint4* lp1 = ldp + ((1+ROTJ)%3)*256*SPR + zr; const uint4* lp2 = ldp + ((2+ROTJ)%3)*256*SPR + zr;
        while ((int)(gtime_v(zr)-G)<0);
        v[0]=ld_cg_v4(lp0); v[1]=ld_cg_v4(lp0+32*SPR);
        while ((int)(gtime_v(zr)-G-pS)<0);
        v[2]=ld_cg_v4(lp1); v[3]=ld_cg_v4(lp1+32*SPR);
        while ((int)(gtime_v(zr)-G-2*pS)<0);
        v[4]=ld_cg_v4(lp2); v[5]=ld_cg_v4(lp2+32*SPR);
        uint32_t cref=0x5000u;
        #pragma unroll
        for (int jj=0;jj<3;jj++){
          #define CVST(u,r) do{ \
            asm volatile("stmatrix.sync.aligned.m8n8.x4.trans.shared.b16 [%0],{%1,%2,%3,%4};"::"r"(sts_mem+jj*384),"r"(h2bf(u.x)),"r"(h2bf(u.y)),"r"(h2bf(u.z)),"r"(h2bf(r.x)):"memory"); \
            asm volatile("stmatrix.sync.aligned.m8n8.x2.trans.shared.b16 [%0],{%1,%2};"::"r"(sts_mem+jj*384+64),"r"(h2bf(r.y)),"r"(h2bf(r.z)):"memory"); }while(0)
          const bool okv = __all_sync(~0u, v[2*jj].w==cref && v[2*jj+1].w==cref);
          CVST(v[2*jj],v[2*jj+1]);
          if (!okv){
            int it=0;
            const uint4* lp = jj==0?lp0:(jj==1?lp1:lp2);
            do { v[2*jj] = ld_cg_v4(lp); v[2*jj+1] = ld_cg_v4(lp + 32*SPR);
              if (RV==2){ if (jj<1){ v[2]=ld_cg_v4(lp1); v[3]=ld_cg_v4(lp1+32*SPR); v[4]=ld_cg_v4(lp2); v[5]=ld_cg_v4(lp2+32*SPR); } } }
            while (!__all_sync(~0u, v[2*jj].w==0x5000u && v[2*jj+1].w==0x5000u) && ++it<(1<<16));
            CVST(v[2*jj],v[2*jj+1]);
          }
          if (jj==2 && tid==256) sts32(ct+56, 0x7f000000u - __float_as_uint(scl));
          bar_arrive(1+jj,384);
          if (jj<2) cref = lds32(ct+40);
        }
        const uint32_t mk = lds32(ct+36);
        uint32_t hm=0;
        #pragma unroll
        for (int q=0;q<6;q++) hm = __vmaxu2(hm, __vmaxu2(__vmaxu2(v[q].x&mk, v[q].y&mk), v[q].z&mk));
        hm = __reduce_max_sync(~0u, max(hm&0xffffu, hm>>16));
        if (lane==0){
          float hf; asm("{.reg .f16 a; mov.b16 a,%1; cvt.f32.f16 %0,a;}":"=f"(hf):"h"((unsigned short)hm));
          sts32(ct+(20+a)*4, __float_as_uint(hf*F(0x7f000000u - __float_as_uint(scl))*1.01f));
        }
      } else { bar_arrive(1,384); bar_arrive(2,384); bar_arrive(3,384);
        if (a==1){
        const unsigned tag=lds32(ct+44); uint4 s0,s1,s2; int it=0;
        do { s0=ld_cg_v4(g_slot+lane); s1=ld_cg_v4(g_slot+32+lane); s2=ld_cg_v4(g_slot+64+lane); if (++it>1) __nanosleep(250); }
        while (!__all_sync(~0u, s0.w==tag && s1.w==tag && s2.w==tag) && it<(1<<20));
        const unsigned gx=__reduce_max_sync(~0u,max(max(s0.x,s1.x),s2.x)), go=__reduce_max_sync(~0u,max(max(s0.y,s1.y),s2.y)), gv=__reduce_max_sync(~0u,max(max(s0.z,s1.z),s2.z));
        if (lane==0){ sts32(ct+60,__float_as_uint(F(gv)*32.f*F(go)*1.1f)); sts32(ct+64,gx); }
        }
      }
      if (s==NSEG-1) break;
      bar_sync(5,128);
      if (tid==256){ mbar_expect(bar_qkv, 4096);
        unsigned tc=gtime();
        if (s>0){ sts32(ct+12, lds32(ct+8)); sts32(ct+8, tlat-lds32(ct+4)); }
        sts32(ct+4,tc);
        asm volatile("st.relaxed.gpu.global.u32 [%0],%1;"::"l"(g_rep + (s&3)*128 + blockIdx.x),"r"((tc + min(lds32(ct+8),lds32(ct+12)))|1u):"memory"); }
      { uint4 hq = lds128(ct+80); float hmx = fmaxf(fmaxf(fmaxf(F(hq.x),F(hq.y)),fmaxf(F(hq.z),F(hq.w))),F(lds32(ct+64)));
        float B = hmx*F(lds32(ct+60)); int eb = (int)((__float_as_uint(B)>>23)&0xff); int es = 127+14+127-eb; es = min(max(es,27),227);
        scl = F((unsigned)es<<23); }
      mbar_wait(bar_kv+8*(s&1), (s>>1)&1);
      bar_sync(8,384);
      const uint32_t kb = sb + lane*16 + SM_KV + (s&1)*16384;
      {
        uint4 kx[4];
        #pragma unroll
        for (int q=0;q<4;q++) ldsm4t(kx[q].x,kx[q].y,kx[q].z,kx[q].w, sb + SM_KV + (s&1)*16384 + (lane&7)*16+((lane>>3)&1)*256+(lane>>4)*128 + (ti*8+4*kh)*512 + ((q^(2*ti))*512));
        mbar_wait(bar_qkv, s&1);
        const uint32_t qb = l8+SM_Q+kh*1024;
        uint2 q0=lds64(qb+ti*512), q1=lds64(qb+ti*512+256), k0=lds64(qb+2048+ti*512), k1=lds64(qb+2048+ti*512+256), q2=lds64(qb+512-ti*512), q3=lds64(qb+768-ti*512);
        float sx0[4]={0,0,0,0}, sx1[4]={0,0,0,0}, sm0[4]={0,0,0,0};
        mma16816(sx0, kx[0].x,kx[0].y,kx[0].z,kx[0].w, q0.x,q0.y);
        mma16816(sx1, kx[1].x,kx[1].y,kx[1].z,kx[1].w, q1.x,q1.y);
        mma16816(sm0, k0.x,k0.x,k0.y,k0.y, q0.x,q0.y);
        mma16816(sx0, kx[2].x,kx[2].y,kx[2].z,kx[2].w, q2.x,q2.y);
        mma16816(sx1, kx[3].x,kx[3].y,kx[3].z,kx[3].w, q3.x,q3.y);
        mma16816(sm0, k1.x,k1.x,k1.y,k1.y, q1.x,q1.y);
        const uint32_t ox = sw0 + (kh*32+ti*16)*4, om = sw0 + (64+16*kh+2*ti)*4;
        stsf(ox, sx0[0]+sx1[0]); stsf(ox+swd, sx0[1]+sx1[1]); stsf(ox+8, sx0[2]+sx1[2]); stsf(ox+swd+8, sx0[3]+sx1[3]);
        stsf(om, sm0[0]); stsf(om+swd, sm0[1]);
      }
      bar_sync(5,128);
      float sc[10];
      {
        uint4 r0=lds128(srd), r2=lds128(srd+128), r1=lds128(srd+64), r3=lds128(srd+192), r4=lds128(srd+256), r5=lds128(srd+320);
        sc[0]=F(r0.x)+F(r2.x); sc[1]=F(r0.y)+F(r2.y); sc[2]=F(r0.z)+F(r2.z); sc[3]=F(r0.w)+F(r2.w);
        sc[4]=F(r1.x)+F(r3.x); sc[5]=F(r1.y)+F(r3.y); sc[6]=F(r1.z)+F(r3.z); sc[7]=F(r1.w)+F(r3.w);
        sc[8]=(F(r4.x)+F(r4.z))+(F(r5.x)+F(r5.z)); sc[9]=(F(r4.y)+F(r4.w))+(F(r5.y)+F(r5.w));
      }
      float mx = fmaxf(fmaxf(fmaxf(sc[0],sc[1]),fmaxf(sc[2],sc[3])),fmaxf(fmaxf(sc[4],sc[5]),fmaxf(sc[6],sc[7])));
      mx = fmaxf(mx,fmaxf(sc[8],sc[9]));
      const uint32_t vb = kb + 8192 + a*2048 + (__float_as_uint(mx) & zr);
      { float m1=__shfl_xor_sync(~0u,mx,1), m2=__shfl_xor_sync(~0u,mx,2), m3=__shfl_xor_sync(~0u,mx,3); mx=fmaxf(fmaxf(mx,m1),fmaxf(m2,m3)); }
      float o0[4]={0,0,0,0}, o1[4]={0,0,0,0}, os[4]={0,0,0,0};
      {
        uint4 v0=lds128(vb), v2=lds128(vb+1024);
        const float mo = mx*cexp;
        const uint32_t ONE=0x3F803F80u;
        const uint32_t P0a=pack2(ex2(fmaf(sc[0],cexp,-mo)),ex2(fmaf(sc[1],cexp,-mo))), P0b=pack2(ex2(fmaf(sc[2],cexp,-mo)),ex2(fmaf(sc[3],cexp,-mo)));
        mma16816(o0, v0.x,v0.y,v0.z,v0.w, P0a,P0b);
        mma16816(o1, v2.x,v2.y,v2.z,v2.w, P0a,P0b);
        mma16816(os, ONE,ONE,ONE,ONE, P0a,P0b);
        uint4 v1=lds128(vb+512), v3=lds128(vb+1536);
        uint2 vf0 = lds64(l8+SM_Q+4096+a*512), vf1 = lds64(l8+SM_Q+4096+a*512+256);
        const uint32_t Pm=pack2(ex2(fmaf(sc[8],cexp,-mo)),ex2(fmaf(sc[9],cexp,-mo)));
        mma1688(o0, vf0.x,vf0.y, Pm);
        mma1688(o1, vf1.x,vf1.y, Pm);
        mma1688(os, ONE,ONE, Pm);
        const uint32_t P1a=pack2(ex2(fmaf(sc[4],cexp,-mo)),ex2(fmaf(sc[5],cexp,-mo))), P1b=pack2(ex2(fmaf(sc[6],cexp,-mo)),ex2(fmaf(sc[7],cexp,-mo)));
        mma16816(o0, v1.x,v1.y,v1.z,v1.w, P1a,P1b);
        mma16816(o1, v3.x,v3.y,v3.z,v3.w, P1a,P1b);
        mma16816(os, ONE,ONE,ONE,ONE, P1a,P1b);
      }
      asm volatile("stmatrix.sync.aligned.m8n8.x4.trans.shared.b16 [%0],{%1,%2,%3,%4};"::"r"(ost+64*a),"r"(pack2(o0[0],o0[1])),"r"(pack2(o0[2],o0[3])),"r"(pack2(o1[0],o1[1])),"r"(pack2(o1[2],o1[3])):"memory");
      uint4 rep = ld_cg_v4((const uint4*)(g_rep + (s&3)*128) + lane);
      bar_sync(6,128);
      float C[3][WOC][4];
      #pragma unroll
      for (int X=0;X<3;X++)
      #pragma unroll
      for (int q=0;q<WOC;q++){ C[X][q][0]=C[X][q][1]=C[X][q][2]=C[X][q][3]=0.f; }
      {
        const uint32_t op = ost | (__float_as_uint(os[0]) & zr);
        #pragma unroll
        for (int q=0;q<4;q++){
          uint32_t b0,b1,b2,b3; ldsm4(b0,b1,b2,b3, op+q*64);
          if (q==WJQ){
            #pragma unroll
            for (int k=8-WJ;k<8;k++)
            #pragma unroll
            for (int X=0;X<3;X++){ uint4 wv=lds128(sb+SM_WJ+lane*16+((a*WJ+k-(8-WJ))*3+X)*512); Wf[X][k][0]=wv.x; Wf[X][k][1]=wv.y; Wf[X][k][2]=wv.z; Wf[X][k][3]=wv.w; }
          }
          #pragma unroll
          for (int X=0;X<3;X++) mma16816(C[X][0], Wf[X][2*q][0],Wf[X][2*q][1],Wf[X][2*q][2],Wf[X][2*q][3], b0,b1);
          #pragma unroll
          for (int X=0;X<3;X++) mma16816(C[X][WOC-1], Wf[X][2*q+1][0],Wf[X][2*q+1][1],Wf[X][2*q+1][2],Wf[X][2*q+1][3], b2,b3);
        }
      }
      if (EB7) bar_arrive(7,384);
      const float i0 = rcpa(os[0])*scl, i1 = rcpa(os[1])*scl;
      uint4* rdp = ap + ((s&(NRING-1))*768 + j*256)*SPR;
      #define CS(X,i) (WOC==2 ? C[X][0][i]+C[X][WOC-1][i] : C[X][0][i])
      { const uint32_t a0=packh(CS(0,0)*i0,CS(0,1)*i1), a1=packh(CS(0,2)*i0,CS(0,3)*i1), a2=packh(CS(1,0)*i0,CS(1,1)*i1), b0=packh(CS(1,2)*i0,CS(1,3)*i1), b1=packh(CS(2,0)*i0,CS(2,1)*i1), b2=packh(CS(2,2)*i0,CS(2,3)*i1);
        if (ROT && (h&1)){ red_h4(rdp+32*SPR,b0,b1,b2,0x3C00u); red_h4(rdp,a0,a1,a2,0x3C00u); }
        else { red_h4(rdp,a0,a1,a2,0x3C00u); red_h4(rdp+32*SPR,b0,b1,b2,0x3C00u); } }
      if (!EB7) bar_arrive(7,384);
      const unsigned tr = gtime_v(zr);
      tlat = tr;
      { int d = max(max(rep.x?(int)(rep.x-tr):0, rep.y?(int)(rep.y-tr):0), max(rep.z?(int)(rep.z-tr):0, rep.w?(int)(rep.w-tr):0));
        d = __reduce_max_sync(~0u, min(d,4000));
        G = tr + d + pK; }
    }
    if (tid==256 && blockIdx.x==0) atomicAdd(&g_epoch,1);
  }
}
__device__ __forceinline__ unsigned ld_acq(const unsigned* p){ unsigned v; asm volatile("ld.acquire.gpu.global.u32 %0,[%1];":"=r"(v):"l"(p):"memory"); return v; }
__device__ __forceinline__ void wait_cnt(const unsigned* p, unsigned target){ int it=0; while (ld_acq(p) < target && ++it<(1<<22)) __nanosleep(40); }
__device__ __forceinline__ void signal_cnt(unsigned* p){ asm volatile("red.relaxed.gpu.global.add.u32 [%0],1;"::"l"(p):"memory"); }
__device__ __forceinline__ void ldsm2t(uint32_t& r0,uint32_t& r1,uint32_t addr){
  asm volatile("ldmatrix.sync.aligned.m8n8.x2.trans.shared.b16 {%0,%1},[%2];":"=r"(r0),"=r"(r1):"r"(addr):"memory");
}
#define R8(d,o) "+f"(d[o]),"+f"(d[o+1]),"+f"(d[o+2]),"+f"(d[o+3]),"+f"(d[o+4]),"+f"(d[o+5]),"+f"(d[o+6]),"+f"(d[o+7])
__device__ __forceinline__ void wgmma_ss_n192(float* d, uint64_t da, uint64_t db, int scale_d){
  asm volatile("{.reg .pred p; setp.ne.b32 p, %98, 0;\n"
   "wgmma.mma_async.sync.aligned.m64n192k16.f32.bf16.bf16 {%0,%1,%2,%3,%4,%5,%6,%7,%8,%9,%10,%11,%12,%13,%14,%15,%16,%17,%18,%19,%20,%21,%22,%23,%24,%25,%26,%27,%28,%29,%30,%31,%32,%33,%34,%35,%36,%37,%38,%39,%40,%41,%42,%43,%44,%45,%46,%47,"
   "%48,%49,%50,%51,%52,%53,%54,%55,%56,%57,%58,%59,%60,%61,%62,%63,%64,%65,%66,%67,%68,%69,%70,%71,%72,%73,%74,%75,%76,%77,%78,%79,%80,%81,%82,%83,%84,%85,%86,%87,%88,%89,%90,%91,%92,%93,%94,%95}, %96, %97, p, 1, 1, 0, 1;}"
   : R8(d,0),R8(d,8),R8(d,16),R8(d,24),R8(d,32),R8(d,40),R8(d,48),R8(d,56),R8(d,64),R8(d,72),R8(d,80),R8(d,88)
   : "l"(da),"l"(db),"r"(scale_d));
}
__device__ __forceinline__ void wgmma_ss_n96(float* d, uint64_t da, uint64_t db, int scale_d){
  asm volatile("{.reg .pred p; setp.ne.b32 p, %50, 0;\n"
   "wgmma.mma_async.sync.aligned.m64n96k16.f32.bf16.bf16 {%0,%1,%2,%3,%4,%5,%6,%7,%8,%9,%10,%11,%12,%13,%14,%15,%16,%17,%18,%19,%20,%21,%22,%23,%24,%25,%26,%27,%28,%29,%30,%31,%32,%33,%34,%35,%36,%37,%38,%39,%40,%41,%42,%43,%44,%45,%46,%47}, %48, %49, p, 1, 1, 0, 1;}"
   : R8(d,0),R8(d,8),R8(d,16),R8(d,24),R8(d,32),R8(d,40)
   : "l"(da),"l"(db),"r"(scale_d));
}

template<bool B> struct BoolC{ static constexpr bool value=B; };
struct AuxMaps { CUtensorMap x128, ao, ao64, ao96, ao32, wo, wob, wo32, wob32, wqkv, out; };


__device__ __forceinline__ void release_slot(uint32_t sb, uint32_t rdelta, int st, int lane){
  if (lane<2) asm volatile("mbarrier.arrive.shared::cluster.b64 _, [%0];"::"r"(sb+A_BAR+32+st*8+(lane?rdelta:0u)):"memory");
}
__device__ __forceinline__ void gemm_main(float* acc, uint32_t sb, uint32_t rdelta, unsigned& it, int nk, int wg, int lane){
  #pragma unroll
  for (int i=0;i<144;i++) acc[i]=0.f;
  for (int i=0;i<nk;i++,it++){
    const int st=it%A_NST;
    mbar_wait(sb+A_BAR+st*8, (it/A_NST)&1);
    const uint64_t da = ((uint64_t)(((sb+st*A_STAGE+wg*8192)&0x3FFFF)>>4)) | ((uint64_t)1<<16) | ((uint64_t)(1024>>4)<<32) | ((uint64_t)1<<62);
    const uint64_t db = ((uint64_t)(((sb+st*A_STAGE+16384)&0x3FFFF)>>4)) | ((uint64_t)(8192>>4)<<16) | ((uint64_t)(1024>>4)<<32) | ((uint64_t)1<<62);
    asm volatile("wgmma.fence.sync.aligned;":::"memory");
    #pragma unroll
    for (int k=0;k<4;k++){
      wgmma_ss_n192(acc, da+k*2, db+k*128, 1);
      wgmma_ss_n96(acc+96, da+k*2, db+k*128+(3*8192>>4), 1);
    }
    asm volatile("wgmma.commit_group.sync.aligned;":::"memory");
    if (i>0){
      asm volatile("wgmma.wait_group.sync.aligned 1;":::"memory");
      release_slot(sb,rdelta,(it-1)%A_NST,lane);
    }
  }
  asm volatile("wgmma.wait_group.sync.aligned 0;":::"memory");
  release_slot(sb,rdelta,(it-1)%A_NST,lane);
}

__global__ void __cluster_dims__(2,1,1) __launch_bounds__(384,1)
aux_kernel(const __grid_constant__ AuxMaps tm, bf16* __restrict__ out)
{
  extern __shared__ __align__(1024) unsigned char sm[];
  const uint32_t sb = smem_u32(sm);
  const int tid=threadIdx.x, lane=tid&31, w=__shfl_sync(~0u,tid>>5,0), g=lane>>2, t=lane&3;
  const uint32_t cb = sb + A_BAR;
  const int rk = blockIdx.x&1;
  const uint32_t rdelta = mapa(sb, rk^1) - sb;
  int task0=0;
  if (tid==256 && rk==0) task0=atomicAdd(&g_cnt[C_QH],1);
  if (tid==0){ for (int i=0;i<A_NST;i++){ mbar_init(cb+i*8,1); mbar_init(cb+32+i*8,16);} for (int i=0;i<2;i++){ mbar_init(cb+64+i*8,1); mbar_init(cb+80+i*8,8); mbar_init(cb+160+i*8,1); mbar_init(cb+176+i*8,1);} asm volatile("fence.mbarrier_init.release.cluster;":::"memory"); }
  asm volatile("barrier.cluster.arrive.release.aligned;\nbarrier.cluster.wait.acquire.aligned;":::"memory");
  if (w>=8){
   asm volatile("setmaxnreg.dec.sync.aligned.u32 56;");
   if (w==10 && lane<(int)(sizeof(AuxMaps)/sizeof(CUtensorMap))) asm volatile("prefetch.tensormap [%0];"::"l"((uint64_t)((const CUtensorMap*)&tm+lane)):"memory");
   if (w==8){
    if (lane==0){
      unsigned it=0, tn=0; int ltask=0;
      while (true){
        int task;
        if (rk==0){
          if (ltask>=NTASK-NOAHEAD && it>0) mbar_wait(cb+32+((it-1)%A_NST)*8, ((it-1)/A_NST)&1);
          task = tn ? (int)atomicAdd(&g_cnt[C_QH],1) : task0; ltask=task;
          mbar_wait(cb+176+(tn&1)*8, ((tn>>1)&1)^1);
          asm volatile("st.async.shared::cluster.mbarrier::complete_tx::bytes.b32 [%0], %1, [%2];"::"r"(cb+192+(tn&1)*4+rdelta),"r"(task),"r"(cb+160+(tn&1)*8+rdelta):"memory");
        } else {
          mbar_expect(cb+160+(tn&1)*8, 4);
          mbar_wait(cb+160+(tn&1)*8, (tn>>1)&1);
          task = lds32(cb+192+(tn&1)*4);
          asm volatile("mbarrier.arrive.shared::cluster.b64 _, [%0];"::"r"(cb+176+(tn&1)*8+rdelta):"memory");
        }
        const unsigned te = task<NTASK ? c_task[task] : 0u;
        int kind=te&7, p0=0, p1=0, p2=0; bool mcb=true;
        { const int ta=(te>>3)&255, tb=(te>>11)&255, tc=(te>>19)&255, td=te>>27;
          if (kind==K_GATE) p0=ta*2+rk;
          else if (kind==K_BQ){ p0=ta*2+rk; p1=tb; }
          else if (kind==K_BA){ p0=ta; p1=tb*2+rk; }
          else if (kind==K_XA){ p0=ta; p1=(tb*2+rk)*4*tc; p2=tc; }
          else if (kind==K_GM){ p0=((ta>>1)*2+rk)*2+(ta&1); p1=tb|(tc<<8); p2=td; }
          else if (kind==K_GU){ kind=K_GM; mcb=false; p0=ta*2+rk; p1=tb|(tc<<8); p2=td; }
          else if (kind==K_GS){ p0=ta>>2; p1=tb|(tc<<8); p2=((ta&3)*2+rk)|(td<<8); } }
        mbar_wait(cb+80+(tn&1)*8, ((tn>>1)&1)^1);
        { uint32_t d=cb+96+(tn&1)*16; sts32(d,kind|(task<<8)); sts32(d+4,p0); sts32(d+8,p1); sts32(d+12,p2); }
        mbar_arrive(cb+64+(tn&1)*8);
        tn++;
        if (kind==K_END) break;
        #define ACQ() const int st=it%A_NST; mbar_wait(cb+32+st*8, ((it/A_NST)&1)^1); const uint32_t full=cb+st*8, dst=sb+st*A_STAGE; it++;
        if (kind==K_BQ || kind==K_GM){
          const CUtensorMap *tA,*tB0,*tB1; int kbs,kb0,kb1,row0,col0;
          if (kind==K_BQ){ tA=&tm.x128; tB0=tB1=&tm.wqkv; kbs=9; kb0=0; kb1=9; row0=p0*128; col0=p1*288; }
          else { tA=&tm.ao; tB0=&tm.wo; tB1=&tm.wob; kbs=64; kb0=p1&255; kb1=p1>>8; row0=(p0>>1)*128; col0=(p0&1)*288;
            wait_cnt(&g_cnt[(C_RDY+(p0>>1))*32], 24); asm volatile("fence.proxy.async;":::"memory"); }
          for (int kb=kb0;kb<kb1;kb++){
            ACQ();
            mbar_expect(full, A_STAGE);
            const CUtensorMap* tb = kb<kbs ? tB0 : tB1; const int kr=(kb<kbs?kb:kb-kbs)*64;
            if (mcb){
              #pragma unroll
              for (int q=0;q<5;q++) tma_load_2d_mc(dst+16384+q*8192+rk*4096, tb, col0+q*64, kr+rk*32, full, 3);
              tma_load_2d(dst, tA, kb*64, row0, full);
            } else {
              tma_load_2d_mc(dst+rk*8192, &tm.ao64, kb*64, row0+rk*64, full, 3);
              #pragma unroll 1
              for (int q=0;q<10;q++) tma_load_2d(dst+16384+q*4096, tb, col0+(q>>1)*64, kr+(q&1)*32, full);
            }
          }
          for (int i=0;i<2;i++){ ACQ(); (void)dst; mbar_arrive(full); }
        } else if (kind==K_GS){
          const int kb0=p1&255, kb1=p1>>8;
          const unsigned it0=it; const int nt=p2&255; const bool late = p0==15 && kb0<64;
          for (int kk=kb0;kk<kb1;kk+=2){
            ACQ();
            const int n2=min(2,kb1-kk);
            mbar_expect(full, 28672*n2);
            for (int u=0;u<n2;u++){ const int k2=kk+u, kr=(k2<64?k2:k2-64)*64;
              tma_load_3d(dst+u*28672+16384, k2<64?&tm.wo32:&tm.wob32, 0, kr, nt*3, full); }
            if (!late){
              if (kk==kb0){ wait_cnt(&g_cnt[(C_RDY+p0)*32], p0<15?24:8); asm volatile("fence.proxy.async;":::"memory"); }
              if (rk<n2) tma_load_2d_mc(dst+rk*28672, &tm.ao, (kk+rk)*64, p0*128, full, 3);
            }
          }
          if (late){
            const unsigned* xs=&g_cnt[(C_XS+(kb0>>3))*32];
            unsigned f3=0;
            { int sp=0; while (true){ const unsigned f0=ld_flag(xs), f1=ld_flag(xs+256), f2=ld_flag(xs+512); f3=ld_flag(xs+768); if ((ld_acq(&g_cnt[(C_RDY+15)*32])>=8 && f0 && f1 && f2) || ++sp>(1<<22)) break; __nanosleep(40); } }
            asm volatile("fence.proxy.async;":::"memory");
            for (int u=0;u<4;u++){ const int s2=(it0+u)%A_NST; tma_load_2d_mc(sb+s2*A_STAGE+rk*28672, f3?&tm.ao:&tm.ao96, (kb0+2*u+rk)*64, 1920, cb+s2*8, 3); }
            if (!f3){
              { int sp=0; while (ld_acq(xs+768)<1 && ++sp<(1<<22)); }
              asm volatile("fence.proxy.async;":::"memory");
              for (int u=0;u<4;u++){ const int s2=(it0+u)%A_NST; tma_load_2d_mc(sb+s2*A_STAGE+rk*28672+12288, &tm.ao32, (kb0+2*u+rk)*64, 2016, cb+s2*8, 3); }
            }
          }
        } else if (kind==K_BA){
          const int rb=p0, kstart=rb*128-256, kskip=kstart<0?-kstart:0; const uint32_t by=(384-kskip)*48;
          wait_cnt(&g_segflag[0],SEGFLAG_N);
          for (int r=max(rb-2,0);r<=rb;r++) wait_cnt(&g_cnt[(C_BQ+r)*32],6);
          asm volatile("fence.proxy.async;":::"memory");
          for (int i=0;i<4;i++){ const int hh=p1*4+i; ACQ();
            mbar_expect(full, 6144+by+18432);
            for (int f=0;f<kskip;f+=128) bulk_g2s(dst+6144+18432+f*48, g_bq+((size_t)(64+hh)*SEQ)*24, 6144, full);
            bulk_g2s(dst, g_bq+((size_t)hh*SEQ+rb*128)*24, 6144, full);
            bulk_g2s(dst+6144+kskip*48, g_bq+((size_t)(32+hh)*SEQ+kstart+kskip)*24, by, full);
            bulk_g2s(dst+6144+18432+kskip*48, g_bq+((size_t)(64+hh)*SEQ+kstart+kskip)*24, by, full); }
        } else if (kind==K_XA){
          wait_cnt(&g_segflag[(p0>=62?p0-2:p0)*32],SEGFLAG_N);
          asm volatile("fence.proxy.async;":::"memory");
          const unsigned it0=it;
          for (int i=0;i<2*p2;i++){ const size_t b=(size_t)(p0*NH+p1+2*i); ACQ();
            mbar_expect(full, A_STAGE);
            bulk_g2s(dst, g_qx+b*512, 16384, full); bulk_g2s(dst+16384, g_kx+b*512, 16384, full); bulk_g2s(dst+32768, g_vx+b*512, 16384, full);
            if (p0<62){ bulk_g2s(dst+49152, g_km+b*256, 4096, full); bulk_g2s(dst+53248, g_vm+b*256, 4096, full); } }
          if (p0>=62){
            wait_cnt(&g_segflag[p0*32],SEGFLAG_N);
            asm volatile("fence.proxy.async;":::"memory");
            for (int i=0;i<2;i++){ const size_t b=(size_t)(p0*NH+p1+2*i); const int st=(it0+i)%A_NST;
              bulk_g2s(sb+st*A_STAGE+49152, g_km+b*256, 4096, cb+st*8); bulk_g2s(sb+st*A_STAGE+53248, g_vm+b*256, 4096, cb+st*8); }
          }
        }
      }
    }
  } else if (w==9){
    while (true){
      bar_sync(2,288);
      const uint2 cj = lds64(cb+128);
      bar_arrive(3,288);
      if (cj.x==0xffffffffu){ asm volatile("cp.async.bulk.wait_group 0;":::"memory"); break; }
      if (cj.y & 0x40000000u){
        const int s0=cj.y&3, s1=(s0+1)%A_NST;
        if (lane<2 && cj.x!=0xffffu){
          asm volatile("cp.async.bulk.tensor.2d.global.shared::cta.bulk_group [%0, {%2, %3}], [%1];"::"l"((uint64_t)&tm.out),"r"(sb+(lane?s1:s0)*A_STAGE),"r"((int)(cj.x&1)*288+lane*144),"r"((int)(cj.x>>1)*128):"memory");
          asm volatile("cp.async.bulk.commit_group;":::"memory");
          asm volatile("cp.async.bulk.wait_group.read 0;":::"memory");
        }
        __syncwarp();
        asm volatile("mbarrier.arrive.shared::cluster.b64 _, [%0];"::"r"(cb+32+((lane&1)?s1:s0)*8+((lane&2)?rdelta:0u)):"memory");
        continue;
      }
      if (cj.y){
        const int s0=cj.y&3, s1=(s0+1)%A_NST, nt=(cj.y>>8)&7, rb=cj.x-C_BQ;
        for (int r=0;r<16/PACE;r++){
          if (lane<PACE){ const int hl=r*PACE+lane;
            bulk_s2g(g_bq+((size_t)(nt*16+hl)*SEQ+rb*128)*24, sb+(hl<8?s0:s1)*A_STAGE+(hl&7)*6144, 6144);
            asm volatile("cp.async.bulk.commit_group;":::"memory");
            if (PACE<16) asm volatile("cp.async.bulk.wait_group 0;":::"memory"); else asm volatile("cp.async.bulk.wait_group.read 0;":::"memory");
          }
          __syncwarp();
        }
        __syncwarp();
        asm volatile("mbarrier.arrive.shared::cluster.b64 _, [%0];"::"r"(cb+32+((lane&1)?s1:s0)*8+((lane&2)?rdelta:0u)):"memory");
        if (lane<16){ asm volatile("cp.async.bulk.wait_group 0;":::"memory"); asm volatile("fence.proxy.async;":::"memory"); }
        __syncwarp();
      }
      if (lane==0){ __threadfence(); signal_cnt(&g_cnt[cj.x*32]); }
      __syncwarp();
    }
   }
   __syncwarp();
   if (w==11) asm volatile("griddepcontrol.wait;":::"memory");
   asm volatile("barrier.cluster.arrive.relaxed.aligned;\nbarrier.cluster.wait.aligned;":::"memory");
  } else {
    asm volatile("setmaxnreg.inc.sync.aligned.u32 224;");
    unsigned it=0, tn=0; bool sigp=false;
    #define SIGNAL2(c,y) do{ if (sigp) bar_sync(3,288); if (tid==0){ sts32(cb+128,(c)); sts32(cb+132,(y)); } bar_arrive(2,288); sigp=true; }while(0)
    #define SIGNAL(c) SIGNAL2(c,0)
    while (true){
      mbar_wait(cb+64+(tn&1)*8, (tn>>1)&1);
      uint4 td = lds128(cb+96+(tn&1)*16);
      const int kind=__shfl_sync(~0u,td.x&255,0), p0=__shfl_sync(~0u,td.y,0), p1=__shfl_sync(~0u,td.z,0), p2=__shfl_sync(~0u,td.w,0);
      if (lane==0) mbar_arrive(cb+80+(tn&1)*8);
      tn++;
      if (kind==K_END){ SIGNAL(0xffffffffu); asm volatile("barrier.cluster.arrive.relaxed.aligned;\nbarrier.cluster.wait.aligned;":::"memory"); break; }
      if (kind==K_BQ){
        float acc[144];
        gemm_main(acc,sb,rdelta,it,9,w>>2,lane);
        const int s0=it%A_NST, s1=(it+1)%A_NST;
        mbar_wait(cb+s0*8,(it/A_NST)&1); mbar_wait(cb+s1*8,((it+1)/A_NST)&1); it+=2;
        const uint32_t b0=sb+s0*A_STAGE+w*768, b1=sb+s1*A_STAGE+w*768-8*6144;
        const uint32_t padv = p1>=4 ? 0x00003F80u : 0u;
        #pragma unroll
        for (int i=0;i<8;i++){ const int hl=2*i+(lane>>4); uint32_t ad=(hl<8?b0:b1)+hl*6144+(lane&15)*48+36; sts32(ad,padv); sts32(ad+4,0); sts32(ad+8,0); }
        #pragma unroll
        for (int jn=0;jn<36;jn++){
          const int n=8*jn+2*t; const int hl=(n*3641)>>16, d=n-hl*18;
          uint32_t ad = (jn<18?b0:b1) + hl*6144 + g*48 + d*2;
          sts32(ad, pack2(acc[4*jn],acc[4*jn+1])); sts32(ad+8*48, pack2(acc[4*jn+2],acc[4*jn+3]));
        }
        asm volatile("fence.proxy.async.shared::cta;":::"memory");
        SIGNAL2(C_BQ+p0, 0x80000000u|s0|(p1<<8));
      } else if (kind==K_BA){
        const int rb=p0, q0=rb*128+16*w;
        const int imin = q0<256 ? (256-q0)>>4 : 0;
        const float ce = 0.23570226039551584f*1.4426950408889634f, NEG=-INFINITY;
        const uint32_t oq4 = (16*w+(lane&15))*48 + (lane>>4)*16, oq2 = (16*w+(lane&15))*48 + 32;
        const uint32_t ok4 = 6144+(16*w+(lane&7)+((lane>>4)<<3))*48+((lane>>3)&1)*16;
        #define BQK1(S,b,i0,i) { uint32_t k0,k1,k2,k3,k4,k5; ldsm4(k0,k1,k2,k3,b+ok4+(i0+i)*768); ldsm2(k4,k5,b+6144+oq2+(i0+i)*768); \
            _Pragma("unroll") for (int e=0;e<8;e++) S[i][e]=0.f; \
            mma1688(&S[i][0],qa[4],qa[5],k4); mma1688(&S[i][4],qa[4],qa[5],k5); mma16816(&S[i][0],qa[0],qa[1],qa[2],qa[3],k0,k1); mma16816(&S[i][4],qa[0],qa[1],qa[2],qa[3],k2,k3); }
        #define BQK(S,b,i0,n) { _Pragma("unroll") for (int i=0;i<n;i++) BQK1(S,b,i0,i) }
        #define BMAX(S,n,x0,x1) { _Pragma("unroll") for (int i=0;i<n;i++){ x0=fmaxf(x0,fmaxf(fmaxf(S[i][0],S[i][1]),fmaxf(S[i][4],S[i][5]))); x1=fmaxf(x1,fmaxf(fmaxf(S[i][2],S[i][3]),fmaxf(S[i][6],S[i][7]))); } \
            x0=fmaxf(x0,__shfl_xor_sync(~0u,x0,1)); x1=fmaxf(x1,__shfl_xor_sync(~0u,x1,1)); x0=fmaxf(x0,__shfl_xor_sync(~0u,x0,2)); x1=fmaxf(x1,__shfl_xor_sync(~0u,x1,2)); }
        #define BPV1(S,b,i0,i,y0,y1) { { uint32_t v0,v1,v2,v3,v4,v5; ldsm4t(v0,v1,v2,v3,b+6144+18432+oq4+(i0+i)*768); ldsm2t(v4,v5,b+6144+18432+oq2+(i0+i)*768); \
            const uint32_t p0_=pack2(ex2(fmaf(S[i][0],ce,y0)),ex2(fmaf(S[i][1],ce,y0))), p1_=pack2(ex2(fmaf(S[i][2],ce,y1)),ex2(fmaf(S[i][3],ce,y1))); \
            const uint32_t p2_=pack2(ex2(fmaf(S[i][4],ce,y0)),ex2(fmaf(S[i][5],ce,y0))), p3_=pack2(ex2(fmaf(S[i][6],ce,y1)),ex2(fmaf(S[i][7],ce,y1))); \
            mma16816(o[0],p0_,p1_,p2_,p3_,v0,v1); mma16816(o[1],p0_,p1_,p2_,p3_,v2,v3); mma16816(o[2],p0_,p1_,p2_,p3_,v4,v5); } }
        #define BMASK1(S) { _Pragma("unroll") for (int e=0;e<8;e++){ const int c=(e>>2)*8+2*t+(e&1), r=g+((e>>1)&1)*8; if (!(c<=r)) S[7][e]=NEG; } \
            if (EARLY){ _Pragma("unroll") for (int i=0;i<7;i++) if (9+i<imin){ _Pragma("unroll") for (int e=0;e<8;e++) S[i][e]=NEG; } } }
        #define BMASK0(S) { _Pragma("unroll") for (int e=0;e<8;e++){ const int c=(e>>2)*8+2*t+(e&1), r=g+((e>>1)&1)*8; if (!(c>r)) S[0][e]=NEG; } \
            if (EARLY){ _Pragma("unroll") for (int i=0;i<9;i++) if (i<imin){ _Pragma("unroll") for (int e=0;e<8;e++) S[i][e]=NEG; } } }
        auto battn = [&](auto early_c){
          constexpr bool EARLY = decltype(early_c)::value;
          float S1[8][8], S0[9][8], m0=NEG, m1=NEG;
          uint32_t qa[6];
          uint32_t b=sb+(it%A_NST)*A_STAGE;
          mbar_wait(cb+(it%A_NST)*8,(it/A_NST)&1);
          const float g0=1.f-__ldcg(&g_gate[q0+g]), g1=1.f-__ldcg(&g_gate[q0+g+8]);
          ldsm4(qa[0],qa[1],qa[2],qa[3], b+oq4); ldsm2(qa[4],qa[5], b+oq2);
          BQK(S1,b,9,8); BMASK1(S1); BMAX(S1,8,m0,m1);
          #pragma unroll 1
          for (int hi=0;hi<4;hi++,it++){
            float o[3][4];
            #pragma unroll
            for (int c=0;c<3;c++){ o[c][0]=o[c][1]=o[c][2]=o[c][3]=0.f; }
            float n0=m0, n1=m1;
            { const float y0=-m0*ce, y1=-m1*ce;
              _Pragma("unroll") for (int i=0;i<9;i++){ BQK1(S0,b,0,i); if (i<8) BPV1(S1,b,9,(i<8?i:0),y0,y1); } BMASK0(S0); BMAX(S0,9,n0,n1); }
            { const float f0=ex2((m0-n0)*ce), f1=ex2((m1-n1)*ce);
              #pragma unroll
              for (int c=0;c<3;c++){ o[c][0]*=f0; o[c][1]*=f0; o[c][2]*=f1; o[c][3]*=f1; } }
            uint32_t bn=b;
            if (hi<3){ bn=sb+((it+1)%A_NST)*A_STAGE; mbar_wait(cb+((it+1)%A_NST)*8,((it+1)/A_NST)&1); }
            ldsm4(qa[0],qa[1],qa[2],qa[3], bn+oq4); ldsm2(qa[4],qa[5], bn+oq2);
            m0=NEG; m1=NEG;
            { const float y0=-n0*ce, y1=-n1*ce;
              _Pragma("unroll") for (int i=0;i<9;i++){ if (i<8) BQK1(S1,bn,9,(i<8?i:0)); BPV1(S0,b,0,i,y0,y1); } BMASK1(S1); BMAX(S1,8,m0,m1); }
            __syncwarp();
            release_slot(sb,rdelta,it%A_NST,lane);
            const float s0=g0*rcpa(__shfl_sync(~0u,o[2][0],(lane&~3)|1)), s1=g1*rcpa(__shfl_sync(~0u,o[2][2],(lane&~3)|1));
            bf16* dst = g_ao + (size_t)(q0+g)*AOW + 4096 + (p1*4+hi)*18 + 2*t;
            *(uint32_t*)(dst) = pack2(o[0][0]*s0,o[0][1]*s0); *(uint32_t*)(dst+8) = pack2(o[1][0]*s0,o[1][1]*s0);
            *(uint32_t*)(dst+8*AOW) = pack2(o[0][2]*s1,o[0][3]*s1); *(uint32_t*)(dst+8*AOW+8) = pack2(o[1][2]*s1,o[1][3]*s1);
            if (t==0){ *(uint32_t*)(dst+16) = pack2(o[2][0]*s0,o[2][1]*s0); *(uint32_t*)(dst+8*AOW+16) = pack2(o[2][2]*s1,o[2][3]*s1); }
            b=bn;
          }
        };
        if (rb>=6){
          #pragma unroll
          for (int q=0;q<9;q++) __stcg(g_part+(size_t)rb*2*(PSL/4)+(p1*9+q)*256+tid, make_float4(0,0,0,0));
        }
        if (rb<2) battn(BoolC<true>{}); else battn(BoolC<false>{});
        SIGNAL(C_RDY+rb);
      } else if (kind==K_XA){
        const int seg=p0, ti=w&1;
        const int row=seg*32+ti*16+g;
        float ga=0.f, gb=0.f;
        const float NEG=-INFINITY, ce=0.08838834764831845f*1.4426950408889634f;
        for (int half=0;half<p2;half++,it+=2){
          const unsigned mi=it+(w>>2); const int st=mi%A_NST, ot=(it+1-(w>>2))%A_NST;
          mbar_wait(cb+st*8,(mi/A_NST)&1);
          if (half==0){ ga=__ldcg(&g_gate[row]); gb=__ldcg(&g_gate[row+8]); }
          const int hl=(w>>1)&1, h=p1+half*4+(w>>1);
          const uint32_t bq=sb+st*A_STAGE+hl*8192+(lane&7)*16+((lane>>3)&1)*256+(lane>>4)*128;
          const uint32_t b=sb+st*A_STAGE+hl*8192+lane*16, bm=sb+st*A_STAGE+49152+hl*2048+lane*8;
          float S[5][4];
          #pragma unroll
          for (int n=0;n<5;n++){ S[n][0]=S[n][1]=S[n][2]=S[n][3]=0.f; }
          #pragma unroll
          for (int ks=0;ks<8;ks++){
            uint4 q,ka; ldsm4t(q.x,q.y,q.z,q.w,bq+ti*4096+ks*512); ldsm4t(ka.x,ka.z,ka.y,ka.w,b+16384+ks*512); uint2 km=lds64(bm+ks*256);
            mma16816(S[0],q.x,q.y,q.z,q.w,km.x,km.y); mma16816(S[1],q.x,q.y,q.z,q.w,ka.x,ka.z); mma16816(S[2],q.x,q.y,q.z,q.w,ka.y,ka.w);
            if (ti){ uint4 kb; ldsm4t(kb.x,kb.z,kb.y,kb.w,b+16384+4096+ks*512); mma16816(S[3],q.x,q.y,q.z,q.w,kb.x,kb.z); mma16816(S[4],q.x,q.y,q.z,q.w,kb.y,kb.w); }
          }
          #pragma unroll
          for (int n=0;n<4;n++)
          #pragma unroll
          for (int e=0;e<4;e++){ const int c=n*8+2*t+(e&1), r=ti*16+g+(e>>1)*8; if (c>r) S[1+n][e]=NEG; }
          float ma=NEG,mb=NEG;
          #pragma unroll
          for (int n=0;n<5;n++){ ma=fmaxf(ma,fmaxf(S[n][0],S[n][1])); mb=fmaxf(mb,fmaxf(S[n][2],S[n][3])); }
          #pragma unroll
          for (int o=1;o<4;o<<=1){ ma=fmaxf(ma,__shfl_xor_sync(~0u,ma,o)); mb=fmaxf(mb,__shfl_xor_sync(~0u,mb,o)); }
          ma*=-ce; mb*=-ce;
          uint32_t P[5][2]; float sa=0.f,sbb=0.f;
          #pragma unroll
          for (int n=0;n<5;n++){ P[n][0]=pack2(ex2(fmaf(S[n][0],ce,ma)),ex2(fmaf(S[n][1],ce,ma))); P[n][1]=pack2(ex2(fmaf(S[n][2],ce,mb)),ex2(fmaf(S[n][3],ce,mb)));
            sa+=bf_lo(P[n][0])+bf_hi(P[n][0]); sbb+=bf_lo(P[n][1])+bf_hi(P[n][1]); }
          #pragma unroll
          for (int o=1;o<4;o<<=1){ sa+=__shfl_xor_sync(~0u,sa,o); sbb+=__shfl_xor_sync(~0u,sbb,o); }
          sa=ga*rcpa(sa); sbb=gb*rcpa(sbb);
          bf16* dst=g_ao+(size_t)row*AOW+h*128+4*t;
          #pragma unroll
          for (int mt=0;mt<8;mt++){
            float a0[4]={0,0,0,0},a1[4]={0,0,0,0};
            uint4 v0=lds128(b+32768+mt*1024); uint2 vm=lds64(bm+4096+mt*256);
            mma1688(a0,P[0][0],P[0][1],vm.x); mma1688(a1,P[0][0],P[0][1],vm.y);
            mma16816(a0,P[1][0],P[1][1],P[2][0],P[2][1],v0.x,v0.z); mma16816(a1,P[1][0],P[1][1],P[2][0],P[2][1],v0.y,v0.w);
            if (ti){ uint4 v1=lds128(b+32768+mt*1024+512); mma16816(a0,P[3][0],P[3][1],P[4][0],P[4][1],v1.x,v1.z); mma16816(a1,P[3][0],P[3][1],P[4][0],P[4][1],v1.y,v1.w); }
            *(uint2*)(dst+16*mt)        = make_uint2(pack2(a0[0]*sa,a0[1]*sa),pack2(a1[0]*sa,a1[1]*sa));
            *(uint2*)(dst+8*AOW+16*mt)  = make_uint2(pack2(a0[2]*sbb,a0[3]*sbb),pack2(a1[2]*sbb,a1[3]*sbb));
          }
          __syncwarp();
          release_slot(sb,rdelta,st,lane);
          mbar_wait(cb+ot*8,((it+1-(w>>2))/A_NST)&1);
          release_slot(sb,rdelta,ot,lane);
        }
        SIGNAL(seg>=60 ? C_XS+(seg-60)*8+(p1>>2) : C_RDY+(seg>>2));
      } else if (kind==K_GS){
        const int nk=(p1>>8)-(p1&255), wg=w>>2;
        float acc[48];
        #pragma unroll
        for (int i=0;i<48;i++) acc[i]=0.f;
        for (int i=0;i<nk;i++){
          const unsigned ic=it+(i>>1); const int st=ic%A_NST;
          mbar_wait(cb+st*8, (ic/A_NST)&1);
          const uint32_t bs=sb+st*A_STAGE+(i&1)*28672;
          const uint64_t da = ((uint64_t)(((bs+wg*8192)&0x3FFFF)>>4)) | ((uint64_t)1<<16) | ((uint64_t)(1024>>4)<<32) | ((uint64_t)1<<62);
          const uint64_t db = ((uint64_t)(((bs+16384)&0x3FFFF)>>4)) | ((uint64_t)(4096>>4)<<16) | ((uint64_t)(512>>4)<<32) | ((uint64_t)2<<62);
          asm volatile("wgmma.fence.sync.aligned;":::"memory");
          #pragma unroll
          for (int k=0;k<4;k++) wgmma_ss_n96(acc, da+k*2, db+k*64, 1);
          asm volatile("wgmma.commit_group.sync.aligned;":::"memory");
          asm volatile("wgmma.wait_group.sync.aligned 1;":::"memory");
          if (i>0 && !(i&1)) release_slot(sb,rdelta,(ic-1)%A_NST,lane);
        }
        asm volatile("wgmma.wait_group.sync.aligned 0;":::"memory");
        it += (nk+1)>>1;
        release_slot(sb,rdelta,(it-1)%A_NST,lane);
        const int nt=p2&255, ti=(p0-8)*6+nt;
        float4* slab = g_part + (size_t)p0*2*(PSL/4) + nt*3072 + tid;
        #pragma unroll
        for (int q=0;q<12;q++) red_v4(slab+q*256, acc[4*q],acc[4*q+1],acc[4*q+2],acc[4*q+3]);
        __threadfence();
        __syncwarp();
        unsigned old=0;
        if (lane==0) asm volatile("atom.acquire.gpu.global.add.u32 %0,[%1],1;":"=r"(old):"l"(&g_cnt[(C_DONS+ti*8+w)*32]):"memory");
        old=__shfl_sync(~0u,old,0);
        if (old==(unsigned)((p2>>8)-1)){
          float4 p[12];
          #pragma unroll
          for (int q=0;q<12;q++) p[q]=ld_relaxed_v4(slab+q*256);
          bf16* dst = out + (size_t)(p0*128+16*w+g)*DM + nt*96 + 2*t;
          #pragma unroll
          for (int q=0;q<12;q++){ *(uint32_t*)(dst+8*q)=pack2(p[q].x,p[q].y); *(uint32_t*)(dst+8*DM+8*q)=pack2(p[q].z,p[q].w); }
        }
      } else {
        const int tile=p0, nk=(p1>>8)-(p1&255);
        float acc[144];
        gemm_main(acc,sb,rdelta,it,nk,w>>2,lane);
        bool fin=true;
        if (p2>1){
          float4* slab = g_part + (size_t)tile*(PSL/4) + tid;
          #pragma unroll
          for (int q=0;q<36;q++) red_v4(slab+q*256, acc[4*q],acc[4*q+1],acc[4*q+2],acc[4*q+3]);
          __threadfence();
          bar_sync(1,256);
          if (tid==0){ unsigned old=atomicAdd(&g_cnt[(C_DONE+tile)*32],1); __threadfence(); sts32(cb+136,old); }
          bar_sync(1,256);
          fin = (lds32(cb+136)==(unsigned)(p2-1));
          if (fin){
            #pragma unroll
            for (int q=0;q<36;q++){ float4 p=ld_relaxed_v4(slab+q*256); acc[4*q]=p.x; acc[4*q+1]=p.y; acc[4*q+2]=p.z; acc[4*q+3]=p.w; }
          }
        }
        const int s0=it%A_NST, s1=(it+1)%A_NST;
        mbar_wait(cb+s0*8,(it/A_NST)&1); mbar_wait(cb+s1*8,((it+1)/A_NST)&1); it+=2;
        if (fin){
          const uint32_t ro=(16*w+(lane&15))*288+(lane>>4)*16;
          #pragma unroll
          for (int jn=0;jn<36;jn+=2){
            const uint32_t ad = sb+(jn<18?s0:s1)*A_STAGE+ro+(jn%18)*16;
            asm volatile("stmatrix.sync.aligned.m8n8.x4.shared.b16 [%0],{%1,%2,%3,%4};"::"r"(ad),"r"(pack2(acc[4*jn],acc[4*jn+1])),"r"(pack2(acc[4*jn+2],acc[4*jn+3])),"r"(pack2(acc[4*jn+4],acc[4*jn+5])),"r"(pack2(acc[4*jn+6],acc[4*jn+7])):"memory");
          }
          asm volatile("fence.proxy.async.shared::cta;":::"memory");
        }
        SIGNAL2(fin?tile:0xffff, 0x40000000u|s0);
      }
    }
  }
}
typedef CUresult (*EncFn)(CUtensorMap*, CUtensorMapDataType, cuuint32_t, void*, const cuuint64_t*, const cuuint64_t*, const cuuint32_t*, const cuuint32_t*, CUtensorMapInterleave, CUtensorMapSwizzle, CUtensorMapL2promotion, CUtensorMapFloatOOBfill);
static void enc2d(EncFn fn, CUtensorMap* tm, const void* p, uint64_t cols, uint64_t rows, uint32_t bc, uint32_t br, CUtensorMapSwizzle sw=CU_TENSOR_MAP_SWIZZLE_128B){
  cuuint64_t gd[2]={cols,rows}; cuuint64_t gs[1]={cols*2}; cuuint32_t bd[2]={bc,br}; cuuint32_t es[2]={1,1};
  fn(tm,CU_TENSOR_MAP_DATA_TYPE_BFLOAT16,2,(void*)p,gd,gs,bd,es,CU_TENSOR_MAP_INTERLEAVE_NONE,sw,CU_TENSOR_MAP_L2_PROMOTION_L2_128B,CU_TENSOR_MAP_FLOAT_OOB_FILL_NONE);
}
static void enc3d(EncFn fn, CUtensorMap* tm, const void* p, uint64_t cols, uint64_t rows, uint64_t nblk, uint32_t br, uint32_t nb, uint32_t bw=64){
  cuuint64_t gd[3]={bw,rows,nblk}; cuuint64_t gs[2]={cols*2,bw*2}; cuuint32_t bd[3]={bw,br,nb}; cuuint32_t es[3]={1,1,1};
  fn(tm,CU_TENSOR_MAP_DATA_TYPE_BFLOAT16,3,(void*)p,gd,gs,bd,es,CU_TENSOR_MAP_INTERLEAVE_NONE,bw==64?CU_TENSOR_MAP_SWIZZLE_128B:CU_TENSOR_MAP_SWIZZLE_64B,CU_TENSOR_MAP_L2_PROMOTION_L2_128B,CU_TENSOR_MAP_FLOAT_OOB_FILL_NONE);
}
extern "C" void kernel_launch(void* const* d_in, const int* in_sizes, int n_in, void* d_out, int out_size){
  const bf16* x=(const bf16*)d_in[0]; const bf16* mem0=(const bf16*)d_in[1];
  const bf16* Wq=(const bf16*)d_in[2]; const bf16* Wk=(const bf16*)d_in[3]; const bf16* Wv=(const bf16*)d_in[4]; const bf16* Wo=(const bf16*)d_in[5];
  const bf16* wqkv=(const bf16*)d_in[8]; const bf16* wob=(const bf16*)d_in[9]; const bf16* gw=(const bf16*)d_in[10];
  void* fnp=nullptr; cudaDriverEntryPointQueryResult qr;
  cudaGetDriverEntryPoint("cuTensorMapEncodeTiled",&fnp,cudaEnableDefault,&qr);
  EncFn fn=(EncFn)fnp;
  void* ao=nullptr; cudaGetSymbolAddress(&ao,g_ao);
  CUtensorMap tmx; AuxMaps am;
  enc3d(fn,&tmx,x,DM,SEQ,9,32,3);
  enc2d(fn,&am.x128,x,DM,SEQ,64,128);
  enc2d(fn,&am.ao,ao,AOW,SEQ,64,128);
  enc2d(fn,&am.ao64,ao,AOW,SEQ,64,64);
  enc2d(fn,&am.ao32,ao,AOW,SEQ,64,32);
  enc2d(fn,&am.out,d_out,DM,SEQ,144,128,CU_TENSOR_MAP_SWIZZLE_NONE);
  enc2d(fn,&am.wo,Wo,DM,4096,64,32);
  enc3d(fn,&am.wo32,Wo,DM,4096,18,64,3,32);
  enc3d(fn,&am.wob32,wob,DM,DM,18,64,3,32);
  enc2d(fn,&am.ao96,ao,AOW,SEQ,64,96);
  enc2d(fn,&am.wob,wob,DM,DM,64,32);
  enc2d(fn,&am.wqkv,wqkv,1728,DM,64,32);
  cudaFuncSetAttribute(chain_kernel, cudaFuncAttributeMaxDynamicSharedMemorySize, CHAIN_SMEM);
  cudaFuncSetAttribute(aux_kernel, cudaFuncAttributeMaxDynamicSharedMemorySize, AUX_SMEM);
  chain_kernel<<<96,384,CHAIN_SMEM,cudaStreamPerThread>>>(tmx,x,mem0,Wq,Wk,Wv,Wo,gw);
  cudaLaunchConfig_t cfg={}; cfg.gridDim=dim3(132); cfg.blockDim=dim3(384); cfg.dynamicSmemBytes=AUX_SMEM; cfg.stream=cudaStreamPerThread;
  cudaLaunchAttribute at[1]; at[0].id=cudaLaunchAttributeProgrammaticStreamSerialization; at[0].val.programmaticStreamSerializationAllowed=USE_PDL;
  cfg.attrs=at; cfg.numAttrs=1;
  cudaLaunchKernelEx(&cfg, aux_kernel, am, (bf16*)d_out);
}
```
